```python
import torch

def _softmax(x, axis=-1):
    return torch.softmax(x, dim=axis)
def _gelu(x):
    return torch.nn.functional.gelu(x, approximate="tanh")
def _silu(x):
    return torch.nn.functional.silu(x)
def _sigmoid(x):
    return torch.sigmoid(x)
def _layernorm(x, axis=-1, eps=1e-5):
    m = x.mean(dim=axis, keepdim=True)
    v = x.var(dim=axis, keepdim=True, unbiased=False)
    return (x - m) / torch.sqrt(v + eps)
def _scatter_add(tgt, idx, src, axis=0):
    return tgt.clone().index_add_(axis, idx, src)
def _segment_sum(src, seg, n):
    out = torch.zeros((n,) + src.shape[1:], dtype=src.dtype)
    return out.index_add_(0, seg, src)
def _pad(x, pw):
    flat = tuple(v for pair in reversed(pw) for v in pair)
    return torch.nn.functional.pad(x, flat)

kernel_name = 'standalone__softmax_full_bidir__sampling'

def setup_inputs():

    _w = (lambda a: (lambda t: t.to(torch.bfloat16) if t.is_floating_point() else t)(torch.as_tensor(a)))
    B, H, Sq, Skv, Dh = 16, 32, 4, 4096, 128
    return {
        "q": _w((lambda *s: torch.randn(*s, dtype=torch.bfloat16) * 0.8)(B, H, Sq, Dh)),
        "k": _w((lambda *s: torch.randn(*s, dtype=torch.bfloat16) * 0.8)(B, H, Skv, Dh)),
        "v": _w((lambda *s: torch.randn(*s, dtype=torch.bfloat16) * 0.05)(B, H, Skv, Dh)),
    }

def reference(q, k, v):
    scale = q.shape[-1] ** -0.5
    scores = torch.einsum('bhqd,bhkd->bhqk', q, k) * scale
    attn = _softmax(scores, axis=-1)
    return torch.einsum('bhqk,bhkd->bhqd', attn, v)
```

```cpp
#include <cuda_runtime.h>
#include <cuda_bf16.h>
#include <cuda.h>
#include <stdint.h>

namespace {

constexpr int NH      = 512;
constexpr int SQ      = 4;
constexpr int SKV     = 4096;
constexpr int DH      = 128;
constexpr int TILE    = 64;
constexpr int TPH     = SKV / TILE;
constexpr int NSPLIT  = 32;
constexpr int NUNITS  = NH * NSPLIT;
#define NSTAGES 3
constexpr int NST     = NSTAGES;
constexpr int TILE_BYTES = TILE * DH * 2;
constexpr int Q_BYTES = SQ * DH * 2;
#define RING 32
constexpr int RG      = RING;
#define MLAG 360
constexpr int MERGE_LAG = MLAG;
static_assert((NH / RG) % 2 == 0, "generation parity must repeat every launch");
constexpr int MAXSLOT = 8;
constexpr int SSTRIDE = 80;

constexpr int NTHREADS = 288;

constexpr uint32_t F_FIRST = 1u << 16;
constexpr uint32_t F_LAST  = 1u << 17;
constexpr uint32_t F_FIN   = 1u << 18;
constexpr uint32_t F_END   = 1u << 19;

struct __align__(16) SmemTail {
    float    scores[2][SQ * SSTRIDE];
    float    state[MAXSLOT][4][136];
    float    wbuf[4][32][4];
    uint64_t full[NST];
    uint64_t empty[NST];
    uint64_t sready[MAXSLOT];
    uint32_t meta[NST];
    volatile int progress;
};
constexpr int SMEM_BYTES = 1024 + NST * TILE_BYTES + NST * Q_BYTES + (int)sizeof(SmemTail);

__device__ uint4        g_po[RG][4][NSPLIT][32];
__device__ uint4        g_ml[RG][4][NSPLIT][2];
__device__ unsigned int g_merged[RG][4];
__device__ unsigned int g_ctr;
__device__ unsigned int g_done;

__device__ __forceinline__ uint32_t smem_u32(const void* p) { return (uint32_t)__cvta_generic_to_shared(p); }
__device__ __forceinline__ void mbar_init(uint32_t bar, uint32_t cnt) {
    asm volatile("mbarrier.init.shared::cta.b64 [%0], %1;" :: "r"(bar), "r"(cnt));
}
__device__ __forceinline__ void mbar_expect_tx(uint32_t bar, uint32_t bytes) {
    asm volatile("mbarrier.arrive.expect_tx.shared::cta.b64 _, [%0], %1;" :: "r"(bar), "r"(bytes) : "memory");
}
__device__ __forceinline__ void mbar_arrive(uint32_t bar) {
    asm volatile("mbarrier.arrive.shared::cta.b64 _, [%0];" :: "r"(bar) : "memory");
}
__device__ __forceinline__ void mbar_wait(uint32_t bar, uint32_t parity) {
    uint32_t done;
    uint32_t iters = 0;
    do {
        asm volatile("{\n.reg .pred p;\nmbarrier.try_wait.parity.shared::cta.b64 p, [%1], %2;\nselp.u32 %0, 1, 0, p;\n}"
                     : "=r"(done) : "r"(bar), "r"(parity) : "memory");
        if (++iters > (1u << 24)) __trap();
    } while (!done);
}
__device__ __forceinline__ void tma3d(uint32_t dst, const CUtensorMap* m, int row, uint32_t bar, uint64_t pol) {
    asm volatile("cp.async.bulk.tensor.3d.shared::cluster.global.mbarrier::complete_tx::bytes.L2::cache_hint "
                 "[%0], [%1, {%3, %4, %3}], [%2], %5;"
                 :: "r"(dst), "l"(m), "r"(bar), "r"(0), "r"(row), "l"(pol) : "memory");
}
__device__ __forceinline__ void bulk_load(uint32_t dst, const void* src, uint32_t bytes, uint32_t bar) {
    asm volatile("cp.async.bulk.shared::cluster.global.mbarrier::complete_tx::bytes [%0], [%1], %2, [%3];"
                 :: "r"(dst), "l"(src), "r"(bytes), "r"(bar) : "memory");
}
__device__ __forceinline__ void ldsm4(uint32_t& r0, uint32_t& r1, uint32_t& r2, uint32_t& r3, uint32_t addr) {
    asm volatile("ldmatrix.sync.aligned.m8n8.x4.shared.b16 {%0,%1,%2,%3}, [%4];"
                 : "=r"(r0), "=r"(r1), "=r"(r2), "=r"(r3) : "r"(addr) : "memory");
}
__device__ __forceinline__ void ldsm4t(uint32_t& r0, uint32_t& r1, uint32_t& r2, uint32_t& r3, uint32_t addr) {
    asm volatile("ldmatrix.sync.aligned.m8n8.x4.trans.shared.b16 {%0,%1,%2,%3}, [%4];"
                 : "=r"(r0), "=r"(r1), "=r"(r2), "=r"(r3) : "r"(addr) : "memory");
}
__device__ __forceinline__ void mma16816(float (&c)[4], uint32_t a0, uint32_t a1, uint32_t a2, uint32_t a3,
                                         uint32_t b0, uint32_t b1) {
    asm volatile("mma.sync.aligned.m16n8k16.row.col.f32.bf16.bf16.f32 {%0,%1,%2,%3}, {%4,%5,%6,%7}, {%8,%9}, {%0,%1,%2,%3};"
                 : "+f"(c[0]), "+f"(c[1]), "+f"(c[2]), "+f"(c[3])
                 : "r"(a0), "r"(a1), "r"(a2), "r"(a3), "r"(b0), "r"(b1));
}
__device__ __forceinline__ uint32_t pack_bf16(float lo, float hi) {
    uint32_t r;
    asm("cvt.rn.bf16x2.f32 %0, %1, %2;" : "=r"(r) : "f"(hi), "f"(lo));
    return r;
}
__device__ __forceinline__ float ex2(float x) {
    float r;
    asm("ex2.approx.ftz.f32 %0, %1;" : "=f"(r) : "f"(x));
    return r;
}
__device__ __forceinline__ unsigned int ld_acquire(const unsigned int* p) {
    unsigned int v;
    asm volatile("ld.acquire.gpu.global.u32 %0, [%1];" : "=r"(v) : "l"(p) : "memory");
    return v;
}
__device__ __forceinline__ unsigned int ld_relaxed(const unsigned int* p) {
    unsigned int v;
    asm volatile("ld.relaxed.gpu.global.u32 %0, [%1];" : "=r"(v) : "l"(p) : "memory");
    return v;
}
__device__ __forceinline__ void st_release(unsigned int* p, unsigned int v) {
    asm volatile("st.release.gpu.global.u32 [%0], %1;" :: "l"(p), "r"(v) : "memory");
}
__device__ __forceinline__ uint4 ld_relaxed4(const uint4* p) {
    uint4 v;
    asm volatile("ld.relaxed.gpu.global.v4.u32 {%0,%1,%2,%3}, [%4];" : "=r"(v.x), "=r"(v.y), "=r"(v.z), "=r"(v.w) : "l"(p) : "memory");
    return v;
}
__device__ __forceinline__ void st_relaxed4(uint4* p, uint4 v) {
    asm volatile("st.relaxed.gpu.global.v4.u32 [%0], {%1,%2,%3,%4};" :: "l"(p), "r"(v.x), "r"(v.y), "r"(v.z), "r"(v.w) : "memory");
}
__device__ __forceinline__ void st_relaxed(unsigned int* p, unsigned int v) {
    asm volatile("st.relaxed.gpu.global.u32 [%0], %1;" :: "l"(p), "r"(v) : "memory");
}
__device__ __forceinline__ uint32_t tagged(float x, uint32_t tb) { return (__float_as_uint(x) & ~1u) | tb; }

__global__ void __launch_bounds__(NTHREADS, 1)
attn_kernel(const __grid_constant__ CUtensorMap mapK, const __grid_constant__ CUtensorMap mapV,
            const __nv_bfloat16* __restrict__ q, __nv_bfloat16* __restrict__ out)
{
    extern __shared__ unsigned char smem_raw[];
    unsigned char* smem = (unsigned char*)(((uintptr_t)smem_raw + 1023) & ~(uintptr_t)1023);
    unsigned char* qbuf = smem + NST * TILE_BYTES;
    SmemTail* st = (SmemTail*)(qbuf + NST * Q_BYTES);

    const int warp = threadIdx.x >> 5;
    const int lane = threadIdx.x & 31;
    const int G = gridDim.x;
    const int cta = blockIdx.x;
    const float C = 0.08838834764831845f * 1.4426950408889634f;

    if (threadIdx.x == 256) {
        for (int s = 0; s < NST; s++) { mbar_init(smem_u32(&st->full[s]), 1); mbar_init(smem_u32(&st->empty[s]), 4); }
        for (int k = 0; k < MAXSLOT; k++) mbar_init(smem_u32(&st->sready[k]), 4);
        st->progress = 0;
        asm volatile("fence.mbarrier_init.release.cluster;" ::: "memory");
    }
    __syncthreads();

    if (warp == 8) {
        if (lane == 0) {
            uint64_t pol;
            asm volatile("createpolicy.fractional.L2::evict_first.b64 %0, 1.0;" : "=l"(pol));
            int s = 0; uint32_t ph = 1;
            auto issue = [&](int h, int tile, uint32_t meta) {
                const int row = h * SKV + tile * TILE;
                mbar_wait(smem_u32(&st->empty[s]), ph);
                st->meta[s] = meta;
                const uint32_t fb = smem_u32(&st->full[s]);
                if (meta & F_FIRST) {
                    mbar_expect_tx(fb, TILE_BYTES + Q_BYTES);
                    bulk_load(smem_u32(qbuf + s * Q_BYTES), q + (size_t)h * SQ * DH, Q_BYTES, fb);
                } else {
                    mbar_expect_tx(fb, TILE_BYTES);
                }
                tma3d(smem_u32(smem + s * TILE_BYTES), &mapK, row, fb, pol);
                if (++s == NST) { s = 0; ph ^= 1; }
                mbar_wait(smem_u32(&st->empty[s]), ph);
                const uint32_t fb2 = smem_u32(&st->full[s]);
                mbar_expect_tx(fb2, TILE_BYTES);
                tma3d(smem_u32(smem + s * TILE_BYTES), &mapV, row, fb2, pol);
                if (++s == NST) { s = 0; ph ^= 1; }
            };
            int u = cta;
            while (u < NUNITS) {
                const int h = u >> 5, j = u & 31;
                const uint32_t base = (uint32_t)h | ((uint32_t)j << 9);
                int nxt;
                if (j == NSPLIT - 1) {
                    nxt = (int)atomicAdd(&g_ctr, 1u) + G;
                    issue(h, j, base | F_FIRST | F_LAST);
                } else {
                    issue(h, j, base | F_FIRST);
                    nxt = (int)atomicAdd(&g_ctr, 1u) + G;
                    issue(h, j + NSPLIT, base | F_LAST);
                }
                u = nxt;
                st->progress = u;
            }
            int k = 0;
            for (int h = cta; h < NH; h += G, k++) {
                uint32_t meta = (uint32_t)h | ((uint32_t)k << 9) | F_FIRST | F_LAST | F_FIN;
                if (h + G >= NH) meta |= F_END;
                issue(h, TPH - 1, meta);
            }
        }
    } else if (warp >= 4) {
        const int sl = warp - 4;
        const int t = lane & 3;
        int k = 0;
        for (int h = cta; h < NH; h += G, k++) {
            const int slot = h % RG, gen = h / RG;
            const uint32_t tb = (uint32_t)(gen + 1) & 1u;
            {
                const int need = min((h + 1) * NSPLIT + MERGE_LAG, NUNITS);
                uint32_t iters = 0;
                while (st->progress < need) {
                    __nanosleep(200);
                    if (++iters > (1u << 23)) __trap();
                }
            }
            uint4 mu, lu;
            for (uint32_t iters = 0;; iters++) {
                mu = ld_relaxed4(&g_ml[slot][sl][lane][0]);
                lu = ld_relaxed4(&g_ml[slot][sl][lane][1]);
                const uint32_t all1 = mu.x & mu.y & mu.z & mu.w & lu.x & lu.y & lu.z & lu.w;
                const uint32_t any1 = mu.x | mu.y | mu.z | mu.w | lu.x | lu.y | lu.z | lu.w;
                const bool ok = tb ? (all1 & 1u) : !(any1 & 1u);
                if (__all_sync(0xffffffffu, ok)) break;
                __nanosleep(100);
                if (iters > (1u << 21)) __trap();
            }
            uint4 ou[NSPLIT];
#pragma unroll
            for (int j = 0; j < NSPLIT; j++) ou[j] = ld_relaxed4(&g_po[slot][sl][j][lane]);
            const float4 m4 = make_float4(__uint_as_float(mu.x), __uint_as_float(mu.y), __uint_as_float(mu.z), __uint_as_float(mu.w));
            const float4 l4 = make_float4(__uint_as_float(lu.x), __uint_as_float(lu.y), __uint_as_float(lu.z), __uint_as_float(lu.w));
            float4 M = m4;
#pragma unroll
            for (int d = 16; d >= 1; d >>= 1) {
                M.x = fmaxf(M.x, __shfl_xor_sync(0xffffffffu, M.x, d));
                M.y = fmaxf(M.y, __shfl_xor_sync(0xffffffffu, M.y, d));
                M.z = fmaxf(M.z, __shfl_xor_sync(0xffffffffu, M.z, d));
                M.w = fmaxf(M.w, __shfl_xor_sync(0xffffffffu, M.w, d));
            }
            float4 w;
            w.x = ex2((m4.x - M.x) * C); w.y = ex2((m4.y - M.y) * C);
            w.z = ex2((m4.z - M.z) * C); w.w = ex2((m4.w - M.w) * C);
            float4 L = make_float4(w.x * l4.x, w.y * l4.y, w.z * l4.z, w.w * l4.w);
#pragma unroll
            for (int d = 16; d >= 1; d >>= 1) {
                L.x += __shfl_xor_sync(0xffffffffu, L.x, d);
                L.y += __shfl_xor_sync(0xffffffffu, L.y, d);
                L.z += __shfl_xor_sync(0xffffffffu, L.z, d);
                L.w += __shfl_xor_sync(0xffffffffu, L.w, d);
            }
            *(float4*)&st->wbuf[sl][lane][0] = w;
            __syncwarp();
            for (uint32_t iters = 0;; iters++) {
                uint32_t all1 = 0xffffffffu, any1 = 0u;
#pragma unroll
                for (int j = 0; j < NSPLIT; j++) {
                    all1 &= ou[j].x & ou[j].y & ou[j].z & ou[j].w;
                    any1 |= ou[j].x | ou[j].y | ou[j].z | ou[j].w;
                }
                const bool ok = tb ? (all1 & 1u) : !(any1 & 1u);
                if (__all_sync(0xffffffffu, ok)) break;
                if (iters > (1u << 21)) __trap();
#pragma unroll
                for (int j = 0; j < NSPLIT; j++) ou[j] = ld_relaxed4(&g_po[slot][sl][j][lane]);
            }
            float4 acc = make_float4(0.f, 0.f, 0.f, 0.f);
#pragma unroll
            for (int j = 0; j < NSPLIT; j++) {
                const float2 ww = *(const float2*)&st->wbuf[sl][j][2 * (t & 1)];
                acc.x = fmaf(ww.x, __uint_as_float(ou[j].x), acc.x);
                acc.y = fmaf(ww.y, __uint_as_float(ou[j].y), acc.y);
                acc.z = fmaf(ww.x, __uint_as_float(ou[j].z), acc.z);
                acc.w = fmaf(ww.y, __uint_as_float(ou[j].w), acc.w);
            }
            float* stp = &st->state[k][sl][0];
            *(float4*)(stp + lane * 4) = acc;
            if (lane == 0) { *(float4*)(stp + 128) = M; *(float4*)(stp + 132) = L; }
            __syncwarp();
            if (lane == 0) {
                mbar_arrive(smem_u32(&st->sready[k]));
                st_release(&g_merged[slot][sl], (unsigned)gen + 1u);
            }
        }
    } else {
        const int w = warp;
        const int g = lane >> 2, t = lane & 3;
        const int li = lane >> 3, lr = lane & 7;
        uint32_t koff[4];
#pragma unroll
        for (int kp = 0; kp < 4; kp++) {
            const int chunk = 4 * kp + li;
            koff[kp] = (uint32_t)((chunk >> 3) * 8192 + (16 * w + lr) * 128 + (((chunk & 7) ^ lr) << 4));
        }
        uint32_t voff[2];
#pragma unroll
        for (int mt = 0; mt < 2; mt++) {
            const int chunk = 4 * w + 2 * mt + (li & 1);
            voff[mt] = (uint32_t)((chunk >> 3) * 8192 + ((li >> 1) * 8 + lr) * 128 + (((chunk & 7) ^ lr) << 4));
        }
        const uint32_t qoff = (uint32_t)((lr & 3) * 256 + li * 16);
        const uint32_t smem_base = smem_u32(smem);
        const uint32_t qbase = smem_u32(qbuf);

        uint32_t qa[16];
        float acc[2][4];
        float m = 0.f, l = 0.f;
        unsigned int ringflag = 0;
        int s = 0; uint32_t ph = 0;
        int par = 0;
        while (true) {
            mbar_wait(smem_u32(&st->full[s]), ph);
            const uint32_t meta = st->meta[s];
            const int h = meta & 511;
            const int jk = (meta >> 9) & 63;
            if (meta & F_FIRST) {
#pragma unroll
                for (int kp = 0; kp < 4; kp++)
                    ldsm4(qa[4 * kp], qa[4 * kp + 1], qa[4 * kp + 2], qa[4 * kp + 3], qbase + s * Q_BYTES + qoff + kp * 64);
                m = -INFINITY; l = 0.f;
#pragma unroll
                for (int i = 0; i < 4; i++) { acc[0][i] = 0.f; acc[1][i] = 0.f; }
                if (!(meta & F_FIN) && h >= RG) ringflag = ld_relaxed(&g_merged[h % RG][w]);
            }
            float sc[2][4];
#pragma unroll
            for (int i = 0; i < 4; i++) { sc[0][i] = 0.f; sc[1][i] = 0.f; }
            {
                const uint32_t kb_ = smem_base + s * TILE_BYTES;
#pragma unroll
                for (int kp = 0; kp < 4; kp++) {
#pragma unroll
                    for (int nt = 0; nt < 2; nt++) {
                        uint32_t b0, b1, b2, b3;
                        ldsm4(b0, b1, b2, b3, kb_ + koff[kp] + nt * 1024);
                        mma16816(sc[nt], qa[4 * kp], 0u, qa[4 * kp + 1], 0u, b0, b1);
                        mma16816(sc[nt], qa[4 * kp + 2], 0u, qa[4 * kp + 3], 0u, b2, b3);
                    }
                }
            }
            float* sb = st->scores[par];
            if (g < 4) *(float4*)&sb[g * SSTRIDE + 16 * w + 4 * t] = make_float4(sc[0][0], sc[0][1], sc[1][0], sc[1][1]);
            __syncwarp();
            if (lane == 0) mbar_arrive(smem_u32(&st->empty[s]));
            if (++s == NST) { s = 0; ph ^= 1; }
            asm volatile("bar.sync 1, 128;" ::: "memory");
            float4 x[4];
#pragma unroll
            for (int kb = 0; kb < 4; kb++) x[kb] = *(const float4*)&sb[(g & 3) * SSTRIDE + 16 * kb + 4 * t];
            par ^= 1;
            float mt_ = fmaxf(fmaxf(x[0].x, x[0].y), fmaxf(x[0].z, x[0].w));
#pragma unroll
            for (int kb = 1; kb < 4; kb++) mt_ = fmaxf(mt_, fmaxf(fmaxf(x[kb].x, x[kb].y), fmaxf(x[kb].z, x[kb].w)));
            mt_ = fmaxf(mt_, __shfl_xor_sync(0xffffffffu, mt_, 1));
            mt_ = fmaxf(mt_, __shfl_xor_sync(0xffffffffu, mt_, 2));
            const float mn = fmaxf(m, mt_);
            const float alpha = ex2((m - mn) * C);
            m = mn;
            const float mc = -mn * C;
            uint32_t pb[4][2];
            float ls = 0.f;
#pragma unroll
            for (int kb = 0; kb < 4; kb++) {
                const float p0 = ex2(fmaf(x[kb].x, C, mc)), p1 = ex2(fmaf(x[kb].y, C, mc));
                const float p2 = ex2(fmaf(x[kb].z, C, mc)), p3 = ex2(fmaf(x[kb].w, C, mc));
                ls += (p0 + p1) + (p2 + p3);
                pb[kb][0] = pack_bf16(p0, p1);
                pb[kb][1] = pack_bf16(p2, p3);
            }
            l = fmaf(l, alpha, ls);
            const float a0 = __shfl_sync(0xffffffffu, alpha, (2 * (t & 1)) * 4);
            const float a1 = __shfl_sync(0xffffffffu, alpha, (2 * (t & 1) + 1) * 4);
#pragma unroll
            for (int mt = 0; mt < 2; mt++) { acc[mt][0] *= a0; acc[mt][1] *= a1; acc[mt][2] *= a0; acc[mt][3] *= a1; }
            mbar_wait(smem_u32(&st->full[s]), ph);
            {
                const uint32_t vb_ = smem_base + s * TILE_BYTES;
#pragma unroll
                for (int kb = 0; kb < 4; kb++) {
#pragma unroll
                    for (int mt = 0; mt < 2; mt++) {
                        uint32_t r0, r1, r2, r3;
                        ldsm4t(r0, r1, r2, r3, vb_ + voff[mt] + kb * 2048);
                        mma16816(acc[mt], r0, r1, r2, r3, pb[kb][0], pb[kb][1]);
                    }
                }
            }
            __syncwarp();
            if (lane == 0) mbar_arrive(smem_u32(&st->empty[s]));
            if (++s == NST) { s = 0; ph ^= 1; }

            if (meta & F_LAST) {
                float lt = l + __shfl_xor_sync(0xffffffffu, l, 1);
                lt += __shfl_xor_sync(0xffffffffu, lt, 2);
                float4 o;
                if (t < 2) o = make_float4(acc[0][0], acc[0][1], acc[0][2], acc[0][3]);
                else       o = make_float4(acc[1][0], acc[1][1], acc[1][2], acc[1][3]);
                if (!(meta & F_FIN)) {
                    const int slot = h % RG, gen = h / RG;
                    if (gen > 0) {
                        uint32_t iters = 0;
                        while (ringflag != (unsigned)gen) {
                            ringflag = ld_acquire(&g_merged[slot][w]);
                            if (++iters > (1u << 24)) __trap();
                        }
                    }
                    const uint32_t tb = (uint32_t)(gen + 1) & 1u;
                    st_relaxed4(&g_po[slot][w][jk][lane], make_uint4(tagged(o.x, tb), tagged(o.y, tb), tagged(o.z, tb), tagged(o.w, tb)));
                    if (g < 4 && t < 2) st_relaxed((unsigned int*)&g_ml[slot][w][jk][t] + g, tagged(t == 0 ? m : lt, tb));
                } else {
                    mbar_wait(smem_u32(&st->sready[jk]), 0);
                    const float* stp = &st->state[jk][w][0];
                    const float4 so = *(const float4*)(stp + lane * 4);
                    const float Ms = stp[128 + (g & 3)], Ls = stp[132 + (g & 3)];
                    const float mf = fmaxf(Ms, m);
                    const float fa = ex2((Ms - mf) * C), fb = ex2((m - mf) * C);
                    const float inv = 1.0f / fmaf(fa, Ls, fb * lt);
                    const float ca = fa * inv, cb = fb * inv;
                    const int q0 = 2 * (t & 1);
                    const float ca0 = __shfl_sync(0xffffffffu, ca, q0 * 4), ca1 = __shfl_sync(0xffffffffu, ca, (q0 + 1) * 4);
                    const float cb0 = __shfl_sync(0xffffffffu, cb, q0 * 4), cb1 = __shfl_sync(0xffffffffu, cb, (q0 + 1) * 4);
                    const int d = 32 * w + 16 * (t >> 1) + g;
                    __nv_bfloat16* op = out + (size_t)h * SQ * DH;
                    op[q0 * DH + d]           = __float2bfloat16(fmaf(ca0, so.x, cb0 * o.x));
                    op[(q0 + 1) * DH + d]     = __float2bfloat16(fmaf(ca1, so.y, cb1 * o.y));
                    op[q0 * DH + d + 8]       = __float2bfloat16(fmaf(ca0, so.z, cb0 * o.z));
                    op[(q0 + 1) * DH + d + 8] = __float2bfloat16(fmaf(ca1, so.w, cb1 * o.w));
                    if (meta & F_END) break;
                }
            }
        }
    }
    __syncthreads();
    if (threadIdx.x == 0) {
        __threadfence();
        const unsigned int d = atomicAdd(&g_done, 1u);
        if (d == (unsigned)G - 1u) {
            g_ctr = 0; g_done = 0;
        }
    }
}

typedef CUresult (*EncodeFn)(CUtensorMap*, CUtensorMapDataType, cuuint32_t, void*, const cuuint64_t*, const cuuint64_t*,
                             const cuuint32_t*, const cuuint32_t*, CUtensorMapInterleave, CUtensorMapSwizzle,
                             CUtensorMapL2promotion, CUtensorMapFloatOOBfill);

void make_map(EncodeFn enc, CUtensorMap* m, const void* p) {
    cuuint64_t gd[3] = {64, (cuuint64_t)NH * SKV, 2};
    cuuint64_t gs[2] = {256, 128};
    cuuint32_t bd[3] = {64, TILE, 2};
    cuuint32_t es[3] = {1, 1, 1};
    enc(m, CU_TENSOR_MAP_DATA_TYPE_BFLOAT16, 3, const_cast<void*>(p), gd, gs, bd, es, CU_TENSOR_MAP_INTERLEAVE_NONE,
        CU_TENSOR_MAP_SWIZZLE_128B, CU_TENSOR_MAP_L2_PROMOTION_L2_256B, CU_TENSOR_MAP_FLOAT_OOB_FILL_NONE);
}

}

extern "C" void kernel_launch(void* const* d_in, const int* in_sizes, int n_in, void* d_out, int out_size) {
    (void)in_sizes; (void)n_in; (void)out_size;
    static EncodeFn enc = nullptr;
    static int grid = 0;
    if (!enc) {
        cudaDriverEntryPointQueryResult qr;
        cudaGetDriverEntryPoint("cuTensorMapEncodeTiled", (void**)&enc, cudaEnableDefault, &qr);
        int dev = 0, sms = 0;
        cudaGetDevice(&dev);
        cudaDeviceGetAttribute(&sms, cudaDevAttrMultiProcessorCount, dev);
        grid = sms;
        cudaFuncSetAttribute(attn_kernel, cudaFuncAttributeMaxDynamicSharedMemorySize, SMEM_BYTES);
    }
    CUtensorMap mk, mv;
    make_map(enc, &mk, d_in[1]);
    make_map(enc, &mv, d_in[2]);
    attn_kernel<<<grid, NTHREADS, SMEM_BYTES>>>(mk, mv, (const __nv_bfloat16*)d_in[0], (__nv_bfloat16*)d_out);
}
```

```cpp
#include <cuda_runtime.h>
#include <cuda_bf16.h>
#include <cuda.h>
#include <stdint.h>

namespace {

constexpr int NH      = 512;
constexpr int SQ      = 4;
constexpr int SKV     = 4096;
constexpr int DH      = 128;
constexpr int TILE    = 64;
constexpr int TPH     = SKV / TILE;
constexpr int NSPLIT  = 32;
constexpr int NUNITS  = NH * NSPLIT;
#define NSTAGES 3
constexpr int NST     = NSTAGES;
constexpr int TILE_BYTES = TILE * DH * 2;
constexpr int Q_BYTES = SQ * DH * 2;
#define RING 32
constexpr int RG      = RING;
#define MLAG 360
constexpr int MERGE_LAG = MLAG;
static_assert((NH / RG) % 2 == 0, "generation parity must repeat every launch");
constexpr int MAXSLOT = 8;
constexpr int SSTRIDE = 80;

constexpr int NTHREADS = 288;

constexpr uint32_t F_FIRST = 1u << 16;
constexpr uint32_t F_LAST  = 1u << 17;
constexpr uint32_t F_FIN   = 1u << 18;
constexpr uint32_t F_END   = 1u << 19;

struct __align__(16) SmemTail {
    float    scores[2][SQ * SSTRIDE];
    float    state[MAXSLOT][4][136];
    float    wbuf[4][32][4];
    uint64_t full[NST];
    uint64_t empty[NST];
    uint64_t sready[MAXSLOT];
    uint32_t meta[NST];
    volatile int progress;
};
constexpr int SMEM_BYTES = 1024 + NST * TILE_BYTES + NST * Q_BYTES + (int)sizeof(SmemTail);

__device__ uint4        g_po[RG][4][NSPLIT][32];
__device__ uint4        g_ml[RG][4][NSPLIT][2];
__device__ unsigned int g_merged[RG][4];
__device__ unsigned int g_ctr;
__device__ unsigned int g_done;

#define PROF_T(i)
#define PROF_ADD(i, v)

__device__ __forceinline__ uint32_t smem_u32(const void* p) { return (uint32_t)__cvta_generic_to_shared(p); }
__device__ __forceinline__ void mbar_init(uint32_t bar, uint32_t cnt) {
    asm volatile("mbarrier.init.shared::cta.b64 [%0], %1;" :: "r"(bar), "r"(cnt));
}
__device__ __forceinline__ void mbar_expect_tx(uint32_t bar, uint32_t bytes) {
    asm volatile("mbarrier.arrive.expect_tx.shared::cta.b64 _, [%0], %1;" :: "r"(bar), "r"(bytes) : "memory");
}
__device__ __forceinline__ void mbar_arrive(uint32_t bar) {
    asm volatile("mbarrier.arrive.shared::cta.b64 _, [%0];" :: "r"(bar) : "memory");
}
__device__ __forceinline__ void mbar_wait(uint32_t bar, uint32_t parity) {
    uint32_t done;
    uint32_t iters = 0;
    do {
        asm volatile("{\n.reg .pred p;\nmbarrier.try_wait.parity.shared::cta.b64 p, [%1], %2;\nselp.u32 %0, 1, 0, p;\n}"
                     : "=r"(done) : "r"(bar), "r"(parity) : "memory");
        if (++iters > (1u << 24)) __trap();
    } while (!done);
}
__device__ __forceinline__ void tma3d(uint32_t dst, const CUtensorMap* m, int row, uint32_t bar, uint64_t pol) {
    asm volatile("cp.async.bulk.tensor.3d.shared::cluster.global.mbarrier::complete_tx::bytes.L2::cache_hint "
                 "[%0], [%1, {%3, %4, %3}], [%2], %5;"
                 :: "r"(dst), "l"(m), "r"(bar), "r"(0), "r"(row), "l"(pol) : "memory");
}
__device__ __forceinline__ void bulk_load(uint32_t dst, const void* src, uint32_t bytes, uint32_t bar) {
    asm volatile("cp.async.bulk.shared::cluster.global.mbarrier::complete_tx::bytes [%0], [%1], %2, [%3];"
                 :: "r"(dst), "l"(src), "r"(bytes), "r"(bar) : "memory");
}
__device__ __forceinline__ void ldsm4(uint32_t& r0, uint32_t& r1, uint32_t& r2, uint32_t& r3, uint32_t addr) {
    asm volatile("ldmatrix.sync.aligned.m8n8.x4.shared.b16 {%0,%1,%2,%3}, [%4];"
                 : "=r"(r0), "=r"(r1), "=r"(r2), "=r"(r3) : "r"(addr) : "memory");
}
__device__ __forceinline__ void ldsm4t(uint32_t& r0, uint32_t& r1, uint32_t& r2, uint32_t& r3, uint32_t addr) {
    asm volatile("ldmatrix.sync.aligned.m8n8.x4.trans.shared.b16 {%0,%1,%2,%3}, [%4];"
                 : "=r"(r0), "=r"(r1), "=r"(r2), "=r"(r3) : "r"(addr) : "memory");
}
__device__ __forceinline__ void mma16816(float (&c)[4], uint32_t a0, uint32_t a1, uint32_t a2, uint32_t a3,
                                         uint32_t b0, uint32_t b1) {
    asm volatile("mma.sync.aligned.m16n8k16.row.col.f32.bf16.bf16.f32 {%0,%1,%2,%3}, {%4,%5,%6,%7}, {%8,%9}, {%0,%1,%2,%3};"
                 : "+f"(c[0]), "+f"(c[1]), "+f"(c[2]), "+f"(c[3])
                 : "r"(a0), "r"(a1), "r"(a2), "r"(a3), "r"(b0), "r"(b1));
}
__device__ __forceinline__ uint32_t pack_bf16(float lo, float hi) {
    uint32_t r;
    asm("cvt.rn.bf16x2.f32 %0, %1, %2;" : "=r"(r) : "f"(hi), "f"(lo));
    return r;
}
__device__ __forceinline__ float ex2(float x) {
    float r;
    asm("ex2.approx.ftz.f32 %0, %1;" : "=f"(r) : "f"(x));
    return r;
}
__device__ __forceinline__ unsigned int ld_acquire(const unsigned int* p) {
    unsigned int v;
    asm volatile("ld.acquire.gpu.global.u32 %0, [%1];" : "=r"(v) : "l"(p) : "memory");
    return v;
}
__device__ __forceinline__ unsigned int ld_relaxed(const unsigned int* p) {
    unsigned int v;
    asm volatile("ld.relaxed.gpu.global.u32 %0, [%1];" : "=r"(v) : "l"(p) : "memory");
    return v;
}
__device__ __forceinline__ void st_release(unsigned int* p, unsigned int v) {
    asm volatile("st.release.gpu.global.u32 [%0], %1;" :: "l"(p), "r"(v) : "memory");
}
__device__ __forceinline__ uint4 ld_relaxed4(const uint4* p) {
    uint4 v;
    asm volatile("ld.relaxed.gpu.global.v4.u32 {%0,%1,%2,%3}, [%4];" : "=r"(v.x), "=r"(v.y), "=r"(v.z), "=r"(v.w) : "l"(p) : "memory");
    return v;
}
__device__ __forceinline__ void st_relaxed4(uint4* p, uint4 v) {
    asm volatile("st.relaxed.gpu.global.v4.u32 [%0], {%1,%2,%3,%4};" :: "l"(p), "r"(v.x), "r"(v.y), "r"(v.z), "r"(v.w) : "memory");
}
__device__ __forceinline__ void st_relaxed(unsigned int* p, unsigned int v) {
    asm volatile("st.relaxed.gpu.global.u32 [%0], %1;" :: "l"(p), "r"(v) : "memory");
}
__device__ __forceinline__ uint32_t tagged(float x, uint32_t tb) { return (__float_as_uint(x) & ~1u) | tb; }

__global__ void __launch_bounds__(NTHREADS, 1)
attn_kernel(const __grid_constant__ CUtensorMap mapK, const __grid_constant__ CUtensorMap mapV,
            const __nv_bfloat16* __restrict__ q, __nv_bfloat16* __restrict__ out)
{
    extern __shared__ unsigned char smem_raw[];
    unsigned char* smem = (unsigned char*)(((uintptr_t)smem_raw + 1023) & ~(uintptr_t)1023);
    unsigned char* qbuf = smem + NST * TILE_BYTES;
    SmemTail* st = (SmemTail*)(qbuf + NST * Q_BYTES);

    const int warp = threadIdx.x >> 5;
    const int lane = threadIdx.x & 31;
    const int G = gridDim.x;
    const int cta = blockIdx.x;
    const float C = 0.08838834764831845f * 1.4426950408889634f;

    if (threadIdx.x == 256) {
        PROF_T(0);
        for (int s = 0; s < NST; s++) { mbar_init(smem_u32(&st->full[s]), 1); mbar_init(smem_u32(&st->empty[s]), 4); }
        for (int k = 0; k < MAXSLOT; k++) mbar_init(smem_u32(&st->sready[k]), 4);
        st->progress = 0;
        asm volatile("fence.mbarrier_init.release.cluster;" ::: "memory");
    }
    __syncthreads();

    if (warp == 8) {
        if (lane == 0) {
            uint64_t pol;
            asm volatile("createpolicy.fractional.L2::evict_first.b64 %0, 1.0;" : "=l"(pol));
            int s = 0; uint32_t ph = 1;
            auto issue = [&](int h, int tile, uint32_t meta) {
                const int row = h * SKV + tile * TILE;
                mbar_wait(smem_u32(&st->empty[s]), ph);
                st->meta[s] = meta;
                const uint32_t fb = smem_u32(&st->full[s]);
                if (meta & F_FIRST) {
                    mbar_expect_tx(fb, TILE_BYTES + Q_BYTES);
                    bulk_load(smem_u32(qbuf + s * Q_BYTES), q + (size_t)h * SQ * DH, Q_BYTES, fb);
                } else {
                    mbar_expect_tx(fb, TILE_BYTES);
                }
                tma3d(smem_u32(smem + s * TILE_BYTES), &mapK, row, fb, pol);
                if (++s == NST) { s = 0; ph ^= 1; }
                mbar_wait(smem_u32(&st->empty[s]), ph);
                const uint32_t fb2 = smem_u32(&st->full[s]);
                mbar_expect_tx(fb2, TILE_BYTES);
                tma3d(smem_u32(smem + s * TILE_BYTES), &mapV, row, fb2, pol);
                if (++s == NST) { s = 0; ph ^= 1; }
            };
            int u = cta;
            while (u < NUNITS) {
                const int h = u >> 5, j = u & 31;
                const uint32_t base = (uint32_t)h | ((uint32_t)j << 9);
                int nxt;
                if (j == NSPLIT - 1) {
                    nxt = (int)atomicAdd(&g_ctr, 1u) + G;
                    issue(h, j, base | F_FIRST | F_LAST);
                } else {
                    issue(h, j, base | F_FIRST);
                    nxt = (int)atomicAdd(&g_ctr, 1u) + G;
                    issue(h, j + NSPLIT, base | F_LAST);
                }
                u = nxt;
                st->progress = u;
            }
            PROF_T(1);
            int k = 0;
            for (int h = cta; h < NH; h += G, k++) {
                uint32_t meta = (uint32_t)h | ((uint32_t)k << 9) | F_FIRST | F_LAST | F_FIN;
                if (h + G >= NH) meta |= F_END;
                issue(h, TPH - 1, meta);
            }
            PROF_T(2);
        }
    } else if (warp >= 4) {
        const int sl = warp - 4;
        const int t = lane & 3;
        int k = 0;
        for (int h = cta; h < NH; h += G, k++) {
            const int slot = h % RG, gen = h / RG;
            const uint32_t tb = (uint32_t)(gen + 1) & 1u;
            {
                const int need = min((h + 1) * NSPLIT + MERGE_LAG, NUNITS);
                uint32_t iters = 0;
                while (st->progress < need) {
                    __nanosleep(200);
                    if (++iters > (1u << 23)) __trap();
                }
            }
            uint4 mu, lu;
            for (uint32_t iters = 0;; iters++) {
                mu = ld_relaxed4(&g_ml[slot][sl][lane][0]);
                lu = ld_relaxed4(&g_ml[slot][sl][lane][1]);
                const uint32_t all1 = mu.x & mu.y & mu.z & mu.w & lu.x & lu.y & lu.z & lu.w;
                const uint32_t any1 = mu.x | mu.y | mu.z | mu.w | lu.x | lu.y | lu.z | lu.w;
                const bool ok = tb ? (all1 & 1u) : !(any1 & 1u);
                if (__all_sync(0xffffffffu, ok)) break;
                if (lane == 0) { PROF_ADD(5, 1); }
                __nanosleep(100);
                if (iters > (1u << 21)) __trap();
            }
            uint4 ou[NSPLIT];
#pragma unroll
            for (int j = 0; j < NSPLIT; j++) ou[j] = ld_relaxed4(&g_po[slot][sl][j][lane]);
            const float4 m4 = make_float4(__uint_as_float(mu.x), __uint_as_float(mu.y), __uint_as_float(mu.z), __uint_as_float(mu.w));
            const float4 l4 = make_float4(__uint_as_float(lu.x), __uint_as_float(lu.y), __uint_as_float(lu.z), __uint_as_float(lu.w));
            float4 M = m4;
#pragma unroll
            for (int d = 16; d >= 1; d >>= 1) {
                M.x = fmaxf(M.x, __shfl_xor_sync(0xffffffffu, M.x, d));
                M.y = fmaxf(M.y, __shfl_xor_sync(0xffffffffu, M.y, d));
                M.z = fmaxf(M.z, __shfl_xor_sync(0xffffffffu, M.z, d));
                M.w = fmaxf(M.w, __shfl_xor_sync(0xffffffffu, M.w, d));
            }
            float4 w;
            w.x = ex2((m4.x - M.x) * C); w.y = ex2((m4.y - M.y) * C);
            w.z = ex2((m4.z - M.z) * C); w.w = ex2((m4.w - M.w) * C);
            float4 L = make_float4(w.x * l4.x, w.y * l4.y, w.z * l4.z, w.w * l4.w);
#pragma unroll
            for (int d = 16; d >= 1; d >>= 1) {
                L.x += __shfl_xor_sync(0xffffffffu, L.x, d);
                L.y += __shfl_xor_sync(0xffffffffu, L.y, d);
                L.z += __shfl_xor_sync(0xffffffffu, L.z, d);
                L.w += __shfl_xor_sync(0xffffffffu, L.w, d);
            }
            *(float4*)&st->wbuf[sl][lane][0] = w;
            __syncwarp();
            for (uint32_t iters = 0;; iters++) {
                uint32_t all1 = 0xffffffffu, any1 = 0u;
#pragma unroll
                for (int j = 0; j < NSPLIT; j++) {
                    all1 &= ou[j].x & ou[j].y & ou[j].z & ou[j].w;
                    any1 |= ou[j].x | ou[j].y | ou[j].z | ou[j].w;
                }
                const bool ok = tb ? (all1 & 1u) : !(any1 & 1u);
                if (__all_sync(0xffffffffu, ok)) break;
                if (iters > (1u << 21)) __trap();
#pragma unroll
                for (int j = 0; j < NSPLIT; j++) ou[j] = ld_relaxed4(&g_po[slot][sl][j][lane]);
            }
            float4 acc = make_float4(0.f, 0.f, 0.f, 0.f);
#pragma unroll
            for (int j = 0; j < NSPLIT; j++) {
                const float2 ww = *(const float2*)&st->wbuf[sl][j][2 * (t & 1)];
                acc.x = fmaf(ww.x, __uint_as_float(ou[j].x), acc.x);
                acc.y = fmaf(ww.y, __uint_as_float(ou[j].y), acc.y);
                acc.z = fmaf(ww.x, __uint_as_float(ou[j].z), acc.z);
                acc.w = fmaf(ww.y, __uint_as_float(ou[j].w), acc.w);
            }
            float* stp = &st->state[k][sl][0];
            *(float4*)(stp + lane * 4) = acc;
            if (lane == 0) { *(float4*)(stp + 128) = M; *(float4*)(stp + 132) = L; }
            __syncwarp();
            if (lane == 0) {
                mbar_arrive(smem_u32(&st->sready[k]));
                st_release(&g_merged[slot][sl], (unsigned)gen + 1u);
            }
        }
    } else {
        const int w = warp;
        const int g = lane >> 2, t = lane & 3;
        const int li = lane >> 3, lr = lane & 7;
        uint32_t koff[4];
#pragma unroll
        for (int kp = 0; kp < 4; kp++) {
            const int chunk = 4 * kp + li;
            koff[kp] = (uint32_t)((chunk >> 3) * 8192 + (16 * w + lr) * 128 + (((chunk & 7) ^ lr) << 4));
        }
        uint32_t voff[2];
#pragma unroll
        for (int mt = 0; mt < 2; mt++) {
            const int chunk = 4 * w + 2 * mt + (li & 1);
            voff[mt] = (uint32_t)((chunk >> 3) * 8192 + ((li >> 1) * 8 + lr) * 128 + (((chunk & 7) ^ lr) << 4));
        }
        const uint32_t qoff = (uint32_t)((lr & 3) * 256 + li * 16);
        const uint32_t smem_base = smem_u32(smem);
        const uint32_t qbase = smem_u32(qbuf);

        uint32_t qa[16];
        float acc[2][4];
        float m = 0.f, l = 0.f;
        unsigned int ringflag = 0;
        int s = 0; uint32_t ph = 0;
        int par = 0;
        while (true) {
            mbar_wait(smem_u32(&st->full[s]), ph);
            const uint32_t meta = st->meta[s];
            const int h = meta & 511;
            const int jk = (meta >> 9) & 63;
            if (meta & F_FIRST) {
#pragma unroll
                for (int kp = 0; kp < 4; kp++)
                    ldsm4(qa[4 * kp], qa[4 * kp + 1], qa[4 * kp + 2], qa[4 * kp + 3], qbase + s * Q_BYTES + qoff + kp * 64);
                m = -INFINITY; l = 0.f;
#pragma unroll
                for (int i = 0; i < 4; i++) { acc[0][i] = 0.f; acc[1][i] = 0.f; }
                if (!(meta & F_FIN) && h >= RG) ringflag = ld_relaxed(&g_merged[h % RG][w]);
            }
            float sc[2][4];
#pragma unroll
            for (int i = 0; i < 4; i++) { sc[0][i] = 0.f; sc[1][i] = 0.f; }
            {
                const uint32_t kb_ = smem_base + s * TILE_BYTES;
#pragma unroll
                for (int kp = 0; kp < 4; kp++) {
#pragma unroll
                    for (int nt = 0; nt < 2; nt++) {
                        uint32_t b0, b1, b2, b3;
                        ldsm4(b0, b1, b2, b3, kb_ + koff[kp] + nt * 1024);
                        mma16816(sc[nt], qa[4 * kp], 0u, qa[4 * kp + 1], 0u, b0, b1);
                        mma16816(sc[nt], qa[4 * kp + 2], 0u, qa[4 * kp + 3], 0u, b2, b3);
                    }
                }
            }
            float* sb = st->scores[par];
            if (g < 4) *(float4*)&sb[g * SSTRIDE + 16 * w + 4 * t] = make_float4(sc[0][0], sc[0][1], sc[1][0], sc[1][1]);
            __syncwarp();
            if (lane == 0) mbar_arrive(smem_u32(&st->empty[s]));
            if (++s == NST) { s = 0; ph ^= 1; }
            asm volatile("bar.sync 1, 128;" ::: "memory");
            float4 x[4];
#pragma unroll
            for (int kb = 0; kb < 4; kb++) x[kb] = *(const float4*)&sb[(g & 3) * SSTRIDE + 16 * kb + 4 * t];
            par ^= 1;
            float mt_ = fmaxf(fmaxf(x[0].x, x[0].y), fmaxf(x[0].z, x[0].w));
#pragma unroll
            for (int kb = 1; kb < 4; kb++) mt_ = fmaxf(mt_, fmaxf(fmaxf(x[kb].x, x[kb].y), fmaxf(x[kb].z, x[kb].w)));
            mt_ = fmaxf(mt_, __shfl_xor_sync(0xffffffffu, mt_, 1));
            mt_ = fmaxf(mt_, __shfl_xor_sync(0xffffffffu, mt_, 2));
            const float mn = fmaxf(m, mt_);
            const float alpha = ex2((m - mn) * C);
            m = mn;
            const float mc = -mn * C;
            uint32_t pb[4][2];
            float ls = 0.f;
#pragma unroll
            for (int kb = 0; kb < 4; kb++) {
                const float p0 = ex2(fmaf(x[kb].x, C, mc)), p1 = ex2(fmaf(x[kb].y, C, mc));
                const float p2 = ex2(fmaf(x[kb].z, C, mc)), p3 = ex2(fmaf(x[kb].w, C, mc));
                ls += (p0 + p1) + (p2 + p3);
                pb[kb][0] = pack_bf16(p0, p1);
                pb[kb][1] = pack_bf16(p2, p3);
            }
            l = fmaf(l, alpha, ls);
            const float a0 = __shfl_sync(0xffffffffu, alpha, (2 * (t & 1)) * 4);
            const float a1 = __shfl_sync(0xffffffffu, alpha, (2 * (t & 1) + 1) * 4);
#pragma unroll
            for (int mt = 0; mt < 2; mt++) { acc[mt][0] *= a0; acc[mt][1] *= a1; acc[mt][2] *= a0; acc[mt][3] *= a1; }
            mbar_wait(smem_u32(&st->full[s]), ph);
            {
                const uint32_t vb_ = smem_base + s * TILE_BYTES;
#pragma unroll
                for (int kb = 0; kb < 4; kb++) {
#pragma unroll
                    for (int mt = 0; mt < 2; mt++) {
                        uint32_t r0, r1, r2, r3;
                        ldsm4t(r0, r1, r2, r3, vb_ + voff[mt] + kb * 2048);
                        mma16816(acc[mt], r0, r1, r2, r3, pb[kb][0], pb[kb][1]);
                    }
                }
            }
            __syncwarp();
            if (lane == 0) mbar_arrive(smem_u32(&st->empty[s]));
            if (++s == NST) { s = 0; ph ^= 1; }

            if (meta & F_LAST) {
                float lt = l + __shfl_xor_sync(0xffffffffu, l, 1);
                lt += __shfl_xor_sync(0xffffffffu, lt, 2);
                float4 o;
                if (t < 2) o = make_float4(acc[0][0], acc[0][1], acc[0][2], acc[0][3]);
                else       o = make_float4(acc[1][0], acc[1][1], acc[1][2], acc[1][3]);
                if (!(meta & F_FIN)) {
                    const int slot = h % RG, gen = h / RG;
                    if (gen > 0) {
                        uint32_t iters = 0;
                        while (ringflag != (unsigned)gen) {
                            ringflag = ld_acquire(&g_merged[slot][w]);
                            if (lane == 0) { PROF_ADD(6, 1); }
                            if (++iters > (1u << 24)) __trap();
                        }
                    }
                    const uint32_t tb = (uint32_t)(gen + 1) & 1u;
                    st_relaxed4(&g_po[slot][w][jk][lane], make_uint4(tagged(o.x, tb), tagged(o.y, tb), tagged(o.z, tb), tagged(o.w, tb)));
                    if (g < 4 && t < 2) st_relaxed((unsigned int*)&g_ml[slot][w][jk][t] + g, tagged(t == 0 ? m : lt, tb));
                } else {
                    if ((meta & F_END) && threadIdx.x == 0) { PROF_T(3); }
                    mbar_wait(smem_u32(&st->sready[jk]), 0);
                    const float* stp = &st->state[jk][w][0];
                    const float4 so = *(const float4*)(stp + lane * 4);
                    const float Ms = stp[128 + (g & 3)], Ls = stp[132 + (g & 3)];
                    const float mf = fmaxf(Ms, m);
                    const float fa = ex2((Ms - mf) * C), fb = ex2((m - mf) * C);
                    const float inv = 1.0f / fmaf(fa, Ls, fb * lt);
                    const float ca = fa * inv, cb = fb * inv;
                    const int q0 = 2 * (t & 1);
                    const float ca0 = __shfl_sync(0xffffffffu, ca, q0 * 4), ca1 = __shfl_sync(0xffffffffu, ca, (q0 + 1) * 4);
                    const float cb0 = __shfl_sync(0xffffffffu, cb, q0 * 4), cb1 = __shfl_sync(0xffffffffu, cb, (q0 + 1) * 4);
                    const int d = 32 * w + 16 * (t >> 1) + g;
                    __nv_bfloat16* op = out + (size_t)h * SQ * DH;
                    op[q0 * DH + d]           = __float2bfloat16(fmaf(ca0, so.x, cb0 * o.x));
                    op[(q0 + 1) * DH + d]     = __float2bfloat16(fmaf(ca1, so.y, cb1 * o.y));
                    op[q0 * DH + d + 8]       = __float2bfloat16(fmaf(ca0, so.z, cb0 * o.z));
                    op[(q0 + 1) * DH + d + 8] = __float2bfloat16(fmaf(ca1, so.w, cb1 * o.w));
                    if (meta & F_END) break;
                }
            }
        }
    }
    __syncthreads();
    if (threadIdx.x == 0) {
        PROF_T(4);
        __threadfence();
        const unsigned int d = atomicAdd(&g_done, 1u);
        if (d == (unsigned)G - 1u) {
            g_ctr = 0; g_done = 0;
        }
    }
}

typedef CUresult (*EncodeFn)(CUtensorMap*, CUtensorMapDataType, cuuint32_t, void*, const cuuint64_t*, const cuuint64_t*,
                             const cuuint32_t*, const cuuint32_t*, CUtensorMapInterleave, CUtensorMapSwizzle,
                             CUtensorMapL2promotion, CUtensorMapFloatOOBfill);

void make_map(EncodeFn enc, CUtensorMap* m, const void* p) {
    cuuint64_t gd[3] = {64, (cuuint64_t)NH * SKV, 2};
    cuuint64_t gs[2] = {256, 128};
    cuuint32_t bd[3] = {64, TILE, 2};
    cuuint32_t es[3] = {1, 1, 1};
    enc(m, CU_TENSOR_MAP_DATA_TYPE_BFLOAT16, 3, const_cast<void*>(p), gd, gs, bd, es, CU_TENSOR_MAP_INTERLEAVE_NONE,
        CU_TENSOR_MAP_SWIZZLE_128B, CU_TENSOR_MAP_L2_PROMOTION_L2_256B, CU_TENSOR_MAP_FLOAT_OOB_FILL_NONE);
}

}

extern "C" void kernel_launch(void* const* d_in, const int* in_sizes, int n_in, void* d_out, int out_size) {
    (void)in_sizes; (void)n_in; (void)out_size;
    static EncodeFn enc = nullptr;
    static int grid = 0;
    if (!enc) {
        cudaDriverEntryPointQueryResult qr;
        cudaGetDriverEntryPoint("cuTensorMapEncodeTiled", (void**)&enc, cudaEnableDefault, &qr);
        int dev = 0, sms = 0;
        cudaGetDevice(&dev);
        cudaDeviceGetAttribute(&sms, cudaDevAttrMultiProcessorCount, dev);
        grid = sms;
        cudaFuncSetAttribute(attn_kernel, cudaFuncAttributeMaxDynamicSharedMemorySize, SMEM_BYTES);
    }
    CUtensorMap mk, mv;
    make_map(enc, &mk, d_in[1]);
    make_map(enc, &mv, d_in[2]);
    attn_kernel<<<grid, NTHREADS, SMEM_BYTES>>>(mk, mv, (const __nv_bfloat16*)d_in[0], (__nv_bfloat16*)d_out);
}
```

```cpp
#include <cuda_runtime.h>
#include <cuda_bf16.h>
#include <cuda.h>
#include <stdint.h>

namespace {

constexpr int NH      = 512;
constexpr int SQ      = 4;
constexpr int SKV     = 4096;
constexpr int DH      = 128;
constexpr int TILE    = 64;
constexpr int TPH     = SKV / TILE;
constexpr int NREC    = 32;
#define HF2_ 288
constexpr int HF2     = HF2_;
constexpr int NMAIN   = NH * NREC;
constexpr int NTOTAL  = NMAIN + NH;
#define NSTAGES 3
constexpr int NST     = NSTAGES;
constexpr int TILE_BYTES = TILE * DH * 2;
constexpr int Q_BYTES = SQ * DH * 2;
#define RING 64
constexpr int RG      = RING;
#define MLAG 400
constexpr int MERGE_LAG = MLAG;
static_assert((NH / RG) % 2 == 0, "generation parity must repeat every launch");
#define MLAGE 150
constexpr int MERGE_LAG_END = MLAGE;
constexpr int ST_WORDS = 144;
constexpr int ST_BYTES = 4 * ST_WORDS * 4;
constexpr int AUX_BYTES = 3072;
static_assert(AUX_BYTES >= ST_BYTES && AUX_BYTES % 1024 == 0, "aux");

constexpr int NTHREADS = 352;

constexpr uint32_t F_FIRST = 1u << 16;
constexpr uint32_t F_LAST  = 1u << 17;
constexpr uint32_t F_FIN   = 1u << 18;
constexpr uint32_t F_STOP  = 1u << 19;

struct __align__(16) SmemTail {
    uint2    pfrag[NST][4][16];
    float2   xam[NST][4];
    float    xl[NST][4][4];
    float    wmax[2][4][4];
    float    wbuf[2][NREC][4];
    uint64_t full[2][NST];
    uint64_t empty[NST];
    uint64_t mfull[2];
    uint64_t pfree[NST];
    uint32_t meta[NST];
    uint32_t slotK[NST];
    uint32_t slotV[NST];
    uint32_t xmeta[NST];
    volatile int progress;
};
constexpr int MBUF_BYTES = 2 * NREC * 512 + NREC * 32;
constexpr int SMEM_BYTES = 1024 + NST * TILE_BYTES + NST * AUX_BYTES + 2 * MBUF_BYTES + (int)sizeof(SmemTail);

__device__ uint4        g_po[RG][4][NREC][32];
__device__ uint4        g_ml[RG][2][NREC][2];
__device__ uint4        g_state[NH][4][ST_WORDS / 4];
__device__ uint4        g_merged[RG];
__device__ __align__(128) unsigned int g_ctr_[32];
#define g_ctr g_ctr_[0]

#define PROF_T(i)
#define PROF_ADD(i, v)

__device__ __forceinline__ uint32_t smem_u32(const void* p) { return (uint32_t)__cvta_generic_to_shared(p); }
__device__ __forceinline__ void mbar_init(uint32_t bar, uint32_t cnt) {
    asm volatile("mbarrier.init.shared::cta.b64 [%0], %1;" :: "r"(bar), "r"(cnt));
}
__device__ __forceinline__ void mbar_expect_tx(uint32_t bar, uint32_t bytes) {
    asm volatile("mbarrier.arrive.expect_tx.shared::cta.b64 _, [%0], %1;" :: "r"(bar), "r"(bytes) : "memory");
}
__device__ __forceinline__ void mbar_arrive(uint32_t bar) {
    asm volatile("mbarrier.arrive.shared::cta.b64 _, [%0];" :: "r"(bar) : "memory");
}
__device__ __forceinline__ void mbar_wait(uint32_t bar, uint32_t parity) {
    uint32_t done;
    uint32_t iters = 0;
    do {
        asm volatile("{\n.reg .pred p;\nmbarrier.try_wait.parity.shared::cta.b64 p, [%1], %2;\nselp.u32 %0, 1, 0, p;\n}"
                     : "=r"(done) : "r"(bar), "r"(parity) : "memory");
        if (++iters > (1u << 24)) __trap();
    } while (!done);
}
__device__ __forceinline__ uint32_t tile_off(int row, int chunk) {
    return (uint32_t)((chunk >> 3) * 8192 + row * 128 + (((chunk & 7) ^ (row & 7)) << 4));
}
__device__ __forceinline__ void tma3d(uint32_t dst, const CUtensorMap* m, int row, uint32_t bar, uint64_t pol) {
    asm volatile("cp.async.bulk.tensor.3d.shared::cluster.global.mbarrier::complete_tx::bytes.L2::cache_hint "
                 "[%0], [%1, {%3, %4, %3}], [%2], %5;"
                 :: "r"(dst), "l"(m), "r"(bar), "r"(0), "r"(row), "l"(pol) : "memory");
}
__device__ __forceinline__ void tma3d_nohint(uint32_t dst, const CUtensorMap* m, int row, uint32_t bar) {
    asm volatile("cp.async.bulk.tensor.3d.shared::cluster.global.mbarrier::complete_tx::bytes "
                 "[%0], [%1, {%3, %4, %3}], [%2];"
                 :: "r"(dst), "l"(m), "r"(bar), "r"(0), "r"(row) : "memory");
}
__device__ __forceinline__ void bulk_load(uint32_t dst, const void* src, uint32_t bytes, uint32_t bar) {
    asm volatile("cp.async.bulk.shared::cluster.global.mbarrier::complete_tx::bytes [%0], [%1], %2, [%3];"
                 :: "r"(dst), "l"(src), "r"(bytes), "r"(bar) : "memory");
}
__device__ __forceinline__ void ldsm4(uint32_t* r, uint32_t addr) {
    asm volatile("ldmatrix.sync.aligned.m8n8.x4.shared.b16 {%0,%1,%2,%3}, [%4];"
                 : "=r"(r[0]), "=r"(r[1]), "=r"(r[2]), "=r"(r[3]) : "r"(addr) : "memory");
}
__device__ __forceinline__ void ldsm4t(uint32_t* r, uint32_t addr) {
    asm volatile("ldmatrix.sync.aligned.m8n8.x4.trans.shared.b16 {%0,%1,%2,%3}, [%4];"
                 : "=r"(r[0]), "=r"(r[1]), "=r"(r[2]), "=r"(r[3]) : "r"(addr) : "memory");
}
__device__ __forceinline__ uint32_t lds32(uint32_t a) { uint32_t v; asm volatile("ld.shared.u32 %0, [%1];" : "=r"(v) : "r"(a) : "memory"); return v; }
__device__ __forceinline__ uint2 lds64(uint32_t a) { uint2 v; asm volatile("ld.shared.v2.u32 {%0,%1}, [%2];" : "=r"(v.x), "=r"(v.y) : "r"(a) : "memory"); return v; }
__device__ __forceinline__ uint4 lds128(uint32_t a) { uint4 v; asm volatile("ld.shared.v4.u32 {%0,%1,%2,%3}, [%4];" : "=r"(v.x), "=r"(v.y), "=r"(v.z), "=r"(v.w) : "r"(a) : "memory"); return v; }
__device__ __forceinline__ void sts32(uint32_t a, uint32_t v) { asm volatile("st.shared.u32 [%0], %1;" :: "r"(a), "r"(v) : "memory"); }
__device__ __forceinline__ void sts64(uint32_t a, uint32_t x, uint32_t y) { asm volatile("st.shared.v2.u32 [%0], {%1,%2};" :: "r"(a), "r"(x), "r"(y) : "memory"); }
__device__ __forceinline__ void sts32_if(bool c, uint32_t a, uint32_t v) {
    asm volatile("{\n.reg .pred p;\nsetp.ne.u32 p, %2, 0;\n@p st.shared.u32 [%0], %1;\n}" :: "r"(a), "r"(v), "r"((uint32_t)c) : "memory");
}
__device__ __forceinline__ void sts64_if(bool c, uint32_t a, uint32_t x, uint32_t y) {
    asm volatile("{\n.reg .pred p;\nsetp.ne.u32 p, %3, 0;\n@p st.shared.v2.u32 [%0], {%1,%2};\n}" :: "r"(a), "r"(x), "r"(y), "r"((uint32_t)c) : "memory");
}
__device__ __forceinline__ void stg16_if(bool c, void* p, uint32_t v) {
    asm volatile("{\n.reg .pred p;\nsetp.ne.u32 p, %2, 0;\n@p st.global.u16 [%0], %1;\n}" :: "l"(p), "h"((unsigned short)v), "r"((uint32_t)c) : "memory");
}
__device__ __forceinline__ void st_relaxed4_if(bool c, void* p, uint4 v) {
    asm volatile("{\n.reg .pred p;\nsetp.ne.u32 p, %5, 0;\n@p st.relaxed.gpu.global.v4.u32 [%0], {%1,%2,%3,%4};\n}"
                 :: "l"(p), "r"(v.x), "r"(v.y), "r"(v.z), "r"(v.w), "r"((uint32_t)c) : "memory");
}
__device__ __forceinline__ void st_relaxed2_if(bool c, void* p, uint32_t x, uint32_t y) {
    asm volatile("{\n.reg .pred p;\nsetp.ne.u32 p, %3, 0;\n@p st.relaxed.gpu.global.v2.u32 [%0], {%1,%2};\n}"
                 :: "l"(p), "r"(x), "r"(y), "r"((uint32_t)c) : "memory");
}
__device__ __forceinline__ void mbar_arrive_if(bool c, uint32_t bar) {
    asm volatile("{\n.reg .pred p;\nsetp.ne.u32 p, %1, 0;\n@p mbarrier.arrive.shared::cta.b64 _, [%0];\n}" :: "r"(bar), "r"((uint32_t)c) : "memory");
}
__device__ __forceinline__ void mma16816(float (&c)[4], uint32_t a0, uint32_t a1, uint32_t a2, uint32_t a3,
                                         uint32_t b0, uint32_t b1) {
    asm volatile("mma.sync.aligned.m16n8k16.row.col.f32.bf16.bf16.f32 {%0,%1,%2,%3}, {%4,%5,%6,%7}, {%8,%9}, {%0,%1,%2,%3};"
                 : "+f"(c[0]), "+f"(c[1]), "+f"(c[2]), "+f"(c[3])
                 : "r"(a0), "r"(a1), "r"(a2), "r"(a3), "r"(b0), "r"(b1));
}
__device__ __forceinline__ uint32_t pack_bf16(float lo, float hi) {
    uint32_t r;
    asm("cvt.rn.bf16x2.f32 %0, %1, %2;" : "=r"(r) : "f"(hi), "f"(lo));
    return r;
}
__device__ __forceinline__ float ex2(float x) {
    float r;
    asm("ex2.approx.ftz.f32 %0, %1;" : "=f"(r) : "f"(x));
    return r;
}
__device__ __forceinline__ float rcp(float x) {
    float r;
    asm("rcp.approx.ftz.f32 %0, %1;" : "=f"(r) : "f"(x));
    return r;
}
__device__ __forceinline__ unsigned int ld_acquire(const unsigned int* p) {
    unsigned int v;
    asm volatile("ld.acquire.gpu.global.u32 %0, [%1];" : "=r"(v) : "l"(p) : "memory");
    return v;
}
__device__ __forceinline__ uint4 ld_relaxed4(const uint4* p) {
    uint4 v;
    asm volatile("ld.relaxed.gpu.global.v4.u32 {%0,%1,%2,%3}, [%4];" : "=r"(v.x), "=r"(v.y), "=r"(v.z), "=r"(v.w) : "l"(p) : "memory");
    return v;
}
__device__ __forceinline__ uint2 ld_relaxed2(const uint2* p) {
    uint2 v;
    asm volatile("ld.relaxed.gpu.global.v2.u32 {%0,%1}, [%2];" : "=r"(v.x), "=r"(v.y) : "l"(p) : "memory");
    return v;
}
__device__ __forceinline__ void st_relaxed2(uint2* p, uint2 v) {
    asm volatile("st.relaxed.gpu.global.v2.u32 [%0], {%1,%2};" :: "l"(p), "r"(v.x), "r"(v.y) : "memory");
}
__device__ __forceinline__ void st_relaxed4(uint4* p, uint4 v) {
    asm volatile("st.relaxed.gpu.global.v4.u32 [%0], {%1,%2,%3,%4};" :: "l"(p), "r"(v.x), "r"(v.y), "r"(v.z), "r"(v.w) : "memory");
}
__device__ __forceinline__ void st_relaxed(unsigned int* p, unsigned int v) {
    asm volatile("st.relaxed.gpu.global.u32 [%0], %1;" :: "l"(p), "r"(v) : "memory");
}
__device__ __forceinline__ unsigned int atom_inc(unsigned int* p, unsigned int last) {
    unsigned int r;
    asm volatile("atom.relaxed.gpu.global.inc.u32 %0, [%1], %2;" : "=r"(r) : "l"(p), "r"(last) : "memory");
    return r;
}
__device__ __forceinline__ uint32_t tagged(float x, uint32_t tb) { return (__float_as_uint(x) & ~1u) | tb; }
__device__ __forceinline__ uint4 tagged4(float a, float b, float c, float d, uint32_t tb) {
    return make_uint4(tagged(a, tb), tagged(b, tb), tagged(c, tb), tagged(d, tb));
}
__device__ __forceinline__ uint32_t tagdiff(const uint4& v, uint32_t tb) {
    return (v.x ^ tb) | (v.y ^ tb) | (v.z ^ tb) | (v.w ^ tb);
}

__global__ void __launch_bounds__(NTHREADS, 1)
attn_kernel(const __grid_constant__ CUtensorMap mapK, const __grid_constant__ CUtensorMap mapV,
            const __grid_constant__ CUtensorMap mapQ, __nv_bfloat16* __restrict__ out)
{
    extern __shared__ unsigned char smem_raw[];
    unsigned char* smem = (unsigned char*)(((uintptr_t)smem_raw + 1023) & ~(uintptr_t)1023);
    unsigned char* aux = smem + NST * TILE_BYTES;
    unsigned char* mbuf = aux + NST * AUX_BYTES;
    SmemTail* st = (SmemTail*)(mbuf + 2 * MBUF_BYTES);

    const int warp = threadIdx.x >> 5;
    const int lane = threadIdx.x & 31;
    const int G = gridDim.x;
    const int cta = blockIdx.x;
    const float C = 0.08838834764831845f * 1.4426950408889634f;
    const uint32_t smem_base = smem_u32(smem);
    const uint32_t abase = smem_u32(aux);
    const uint32_t fullK = smem_u32(&st->full[0][0]), fullV = smem_u32(&st->full[1][0]), empty0 = smem_u32(&st->empty[0]), meta0 = smem_u32(&st->meta[0]);
    const uint32_t pfree0 = smem_u32(&st->pfree[0]), xmeta0 = smem_u32(&st->xmeta[0]);
    const int g = lane >> 2, t = lane & 3;
    const int li = lane >> 3, lr = lane & 7;

    if (warp < 4) {
        const int w = warp;
        uint32_t koff[4];
#pragma unroll
        for (int kp = 0; kp < 4; kp++) koff[kp] = tile_off(16 * w + lr, 4 * kp + li);
        uint32_t qoff[2];
#pragma unroll
        for (int hf = 0; hf < 2; hf++) qoff[hf] = (uint32_t)((hf * 4 + (lr & 3)) * 128);
        const uint32_t qx[2] = {(uint32_t)(lr & 3), (uint32_t)(4 + (lr & 3))};
        const uint32_t pf_w = smem_u32(&st->pfrag[0][w][(g & 3) * 4 + t]);
        const uint32_t xam_w = smem_u32(&st->xam[0][g & 3]);
        const uint32_t xl_w = smem_u32(&st->xl[0][g & 3][w]);
        const uint32_t wm_r = smem_u32(&st->wmax[0][g & 3][0]);

        uint32_t qa[8][4];
        float m = 0.f, l = 0.f;
        int ik = 0; uint32_t ph = 0;
        uint32_t par = 0;
        asm volatile("bar.sync 2, %0;" :: "n"(NTHREADS) : "memory");
        while (true) {
            mbar_wait(pfree0 + ik * 8, ph ^ 1u);
            mbar_wait(fullK + ik * 8, ph);
            const uint32_t meta = lds32(meta0 + ik * 4);
            const uint32_t s = lds32(meta0 + NST * 4 + ik * 4);
            uint32_t kf[8][4];
            {
                const uint32_t kb_ = smem_base + s * TILE_BYTES;
#pragma unroll
                for (int kp = 0; kp < 4; kp++) {
                    ldsm4(kf[2 * kp], kb_ + koff[kp]);
                    ldsm4(kf[2 * kp + 1], kb_ + koff[kp] + 1024);
                }
            }
            if (meta & F_FIRST) {
                const uint32_t ab = abase + s * AUX_BYTES;
#pragma unroll
                for (int ks = 0; ks < 8; ks++)
                    ldsm4(qa[ks], ab + qoff[ks >> 2] + ((((uint32_t)((2 * ks) & 7) + (uint32_t)(li >> 1)) ^ qx[ks >> 2]) << 4));
                m = -INFINITY; l = 0.f;
            }
            __syncwarp();
            mbar_arrive_if(lane == 0 && !(meta & F_STOP), empty0 + s * 8);
            float sc[4][4];
#pragma unroll
            for (int i = 0; i < 4; i++) { sc[i][0] = 0.f; sc[i][1] = 0.f; sc[i][2] = 0.f; sc[i][3] = 0.f; }
#pragma unroll
            for (int kp = 0; kp < 4; kp++) {
#pragma unroll
                for (int nt = 0; nt < 2; nt++) {
                    mma16816(sc[nt], qa[2 * kp][0], qa[2 * kp][1], qa[2 * kp][2], qa[2 * kp][3], kf[2 * kp + nt][0], kf[2 * kp + nt][1]);
                    mma16816(sc[2 + nt], qa[2 * kp + 1][0], qa[2 * kp + 1][1], qa[2 * kp + 1][2], qa[2 * kp + 1][3], kf[2 * kp + nt][2], kf[2 * kp + nt][3]);
                }
            }
            const float s0 = sc[0][0] + sc[2][0], s1 = sc[0][1] + sc[2][1], s2 = sc[1][0] + sc[3][0], s3 = sc[1][1] + sc[3][1];
            float mt_ = fmaxf(fmaxf(s0, s1), fmaxf(s2, s3));
            mt_ = fmaxf(mt_, __shfl_xor_sync(0xffffffffu, mt_, 1));
            mt_ = fmaxf(mt_, __shfl_xor_sync(0xffffffffu, mt_, 2));
            sts32_if(g < 4 && t == 0, wm_r + par * 64 + w * 4, __float_as_uint(mt_));
            asm volatile("bar.sync 1, 128;" ::: "memory");
            const uint4 wm = lds128(wm_r + par * 64);
            par ^= 1u;
            const float mn = fmaxf(fmaxf(m, fmaxf(__uint_as_float(wm.x), __uint_as_float(wm.y))), fmaxf(__uint_as_float(wm.z), __uint_as_float(wm.w)));
            const float mc = -mn * C;
            const float alpha = ex2(fmaf(m, C, mc));
            m = mn;
            const float p0 = ex2(fmaf(s0, C, mc)), p1 = ex2(fmaf(s1, C, mc)), p2 = ex2(fmaf(s2, C, mc)), p3 = ex2(fmaf(s3, C, mc));
            l = fmaf(l, alpha, (p0 + p1) + (p2 + p3));
            float lt = l + __shfl_xor_sync(0xffffffffu, l, 1);
            sts64_if(g < 4, pf_w + ik * 512, pack_bf16(p0, p1), pack_bf16(p2, p3));
            sts64_if(w == 0 && g < 4 && t == 0, xam_w + ik * 32, __float_as_uint(alpha), __float_as_uint(mn));
            sts32_if(threadIdx.x == 31, xmeta0 + ik * 4, meta);
            lt += __shfl_xor_sync(0xffffffffu, lt, 2);
            sts32_if(g < 4 && t == 0, xl_w + ik * 64, __float_as_uint(lt));
            __syncwarp();
            mbar_arrive_if(lane == 0, fullV + ik * 8);
            if (meta & F_STOP) break;
            if (++ik == NST) { ik = 0; ph ^= 1; }
        }
    } else if (warp < 8) {
        const int w = warp - 4;
        uint32_t voff[2];
#pragma unroll
        for (int mt = 0; mt < 2; mt++) voff[mt] = tile_off((li >> 1) * 8 + lr, 4 * w + 2 * mt + (li & 1));
        const uint32_t pf_r = smem_u32(&st->pfrag[0][0][(g & 3) * 4 + t]);
        const uint32_t xam_r = smem_u32(&st->xam[0][2 * (t & 1)]);
        const uint32_t xl_r = smem_u32(&st->xl[0][2 * (t & 1)][0]);

        float acc[2][2][4];
        int iv = 0; uint32_t ph = 0;
        asm volatile("bar.sync 2, %0;" :: "n"(NTHREADS) : "memory");
        while (true) {
            mbar_wait(fullV + iv * 8, ph);
            const uint32_t s = lds32(meta0 + 2 * NST * 4 + iv * 4);
            const uint32_t meta = lds32(xmeta0 + iv * 4);
            const uint4 am = lds128(xam_r + iv * 32);
            const uint4 l0 = lds128(xl_r + iv * 64), l1 = lds128(xl_r + iv * 64 + 16);
            uint2 pb[4];
#pragma unroll
            for (int kb = 0; kb < 4; kb++) pb[kb] = lds64(pf_r + iv * 512 + kb * 128);
            const uint32_t ab = abase + s * AUX_BYTES;
            uint2 sM = lds64(ab + w * ST_WORDS * 4 + 512 + (t & 1) * 8), sL = lds64(ab + w * ST_WORDS * 4 + 528 + (t & 1) * 8);
            uint4 so = lds128(ab + w * ST_WORDS * 4 + lane * 16);
            uint32_t ringflag = lds32(ab + w * 4);
            uint32_t vf[8][4];
            {
                const uint32_t vb_ = smem_base + s * TILE_BYTES;
#pragma unroll
                for (int kb = 0; kb < 4; kb++) {
                    ldsm4t(vf[2 * kb], vb_ + voff[0] + kb * 2048);
                    ldsm4t(vf[2 * kb + 1], vb_ + voff[1] + kb * 2048);
                }
            }
            __syncwarp();
            mbar_arrive_if(lane == 0 && !(meta & F_STOP), empty0 + s * 8);
            mbar_arrive_if(lane == 0, pfree0 + iv * 8);
            if (++iv == NST) { iv = 0; ph ^= 1; }
            const bool first = meta & F_FIRST;
            const bool fin = (meta & (F_FIN | F_LAST)) == (F_FIN | F_LAST);
            const bool part = (meta & (F_FIN | F_LAST)) == F_LAST;
            const int h = meta & 511;
            const int slot = h % RG, gen = h / RG;
            const float a0 = __uint_as_float(am.x), a1 = __uint_as_float(am.z);
#pragma unroll
            for (int mt = 0; mt < 2; mt++) {
                acc[0][mt][0] = first ? 0.f : acc[0][mt][0] * a0; acc[0][mt][1] = first ? 0.f : acc[0][mt][1] * a1;
                acc[0][mt][2] = first ? 0.f : acc[0][mt][2] * a0; acc[0][mt][3] = first ? 0.f : acc[0][mt][3] * a1;
                acc[1][mt][0] = 0.f; acc[1][mt][1] = 0.f; acc[1][mt][2] = 0.f; acc[1][mt][3] = 0.f;
            }
            const float M0 = __uint_as_float(am.y), M1 = __uint_as_float(am.w);
            const float L0 = (__uint_as_float(l0.x) + __uint_as_float(l0.y)) + (__uint_as_float(l0.z) + __uint_as_float(l0.w));
            const float L1 = (__uint_as_float(l1.x) + __uint_as_float(l1.y)) + (__uint_as_float(l1.z) + __uint_as_float(l1.w));
            uint32_t ok = fin ? (so.x & so.y & so.z & so.w & sM.x & sM.y & sL.x & sL.y) : (uint32_t)(!part || gen == 0 || ringflag == (uint32_t)gen);
            ok = __reduce_and_sync(0xffffffffu, ok);
            float ca0, ca1, cb0, cb1;
            auto factors = [&]() {
                const float Ms0 = __uint_as_float(sM.x), Ms1 = __uint_as_float(sM.y);
                const float mf0 = fmaxf(Ms0, M0), mf1 = fmaxf(Ms1, M1);
                const float fa0 = ex2((Ms0 - mf0) * C), fb0 = ex2((M0 - mf0) * C);
                const float fa1 = ex2((Ms1 - mf1) * C), fb1 = ex2((M1 - mf1) * C);
                const float inv0 = rcp(fmaf(fa0, __uint_as_float(sL.x), fb0 * L0));
                const float inv1 = rcp(fmaf(fa1, __uint_as_float(sL.y), fb1 * L1));
                ca0 = fa0 * inv0; ca1 = fa1 * inv1; cb0 = fb0 * inv0; cb1 = fb1 * inv1;
            };
            factors();
#pragma unroll
            for (int kb = 0; kb < 4; kb++) {
#pragma unroll
                for (int mt = 0; mt < 2; mt++)
                    mma16816(acc[kb & 1][mt], vf[2 * kb + mt][0], vf[2 * kb + mt][1], vf[2 * kb + mt][2], vf[2 * kb + mt][3], pb[kb].x, pb[kb].y);
            }
            if (!(ok & 1u) || (meta & F_STOP)) {
                if (meta & F_STOP) break;
                if (fin) {
                    for (uint32_t iters = 0;; iters++) {
                        so = ld_relaxed4(&g_state[h][w][lane]);
                        sM = ld_relaxed2((const uint2*)&g_state[h][w][32] + (t & 1));
                        sL = ld_relaxed2((const uint2*)&g_state[h][w][33] + (t & 1));
                        if (lane == 0) { PROF_ADD(6, 1000); }
                        if (__reduce_and_sync(0xffffffffu, so.x & so.y & so.z & so.w & sM.x & sM.y & sL.x & sL.y) & 1u) break;
                        if (iters > (1u << 22)) __trap();
                    }
                    factors();
                } else {
                    for (uint32_t iters = 0; ld_acquire((const unsigned int*)&g_merged[slot] + w) != (unsigned)gen; iters++) {
                        if (lane == 0) { PROF_ADD(6, 1); }
                        if (iters > (1u << 24)) __trap();
                    }
                }
            }
#pragma unroll
            for (int mt = 0; mt < 2; mt++) {
#pragma unroll
                for (int i = 0; i < 4; i++) acc[0][mt][i] += acc[1][mt][i];
            }
            float4 o;
            o.x = t < 2 ? acc[0][0][0] : acc[0][1][0]; o.y = t < 2 ? acc[0][0][1] : acc[0][1][1];
            o.z = t < 2 ? acc[0][0][2] : acc[0][1][2]; o.w = t < 2 ? acc[0][0][3] : acc[0][1][3];
            {
                __nv_bfloat16* op = out + (size_t)h * SQ * DH + 2 * (t & 1) * DH + 32 * w + 16 * (t >> 1) + g;
                const uint32_t r0 = pack_bf16(fmaf(cb0, o.x, ca0 * __uint_as_float(so.x)), fmaf(cb1, o.y, ca1 * __uint_as_float(so.y)));
                const uint32_t r1 = pack_bf16(fmaf(cb0, o.z, ca0 * __uint_as_float(so.z)), fmaf(cb1, o.w, ca1 * __uint_as_float(so.w)));
                stg16_if(fin, op, r0 & 0xffffu);
                stg16_if(fin, op + DH, r0 >> 16);
                stg16_if(fin, op + 8, r1 & 0xffffu);
                stg16_if(fin, op + DH + 8, r1 >> 16);
                st_relaxed4_if(fin, &g_state[h][w][lane], make_uint4(0, 0, 0, 0));
                st_relaxed4_if(fin && lane < 2, &g_state[h][w][32 + lane], make_uint4(0, 0, 0, 0));
            }
            {
                const int jk = (meta >> 9) & 63;
                const uint32_t tb = (uint32_t)(gen + 1) & 1u;
                st_relaxed4_if(part, &g_po[slot][w][jk][lane], tagged4(o.x, o.y, o.z, o.w, tb));
                st_relaxed2_if(part && g == 0 && !(w & 1), (uint2*)&g_ml[slot][w >> 1][jk][0] + t,
                               tagged(t < 2 ? M0 : L0, tb), tagged(t < 2 ? M1 : L1, tb));
            }
        }
    } else if (warp < 10) {
        asm volatile("bar.sync 2, %0;" :: "n"(NTHREADS) : "memory");
        const int mi = warp - 8;
        const uint32_t mb = smem_u32(mbuf) + mi * MBUF_BYTES;
        const uint32_t mbar = smem_u32(&st->mfull[mi]);
        const uint32_t wb = smem_u32(&st->wbuf[mi][0][0]);
        uint32_t mph = 0;
        for (int h = cta; h < NH; h += G) {
            const int slot = h % RG, gen = h / RG;
            const uint32_t tb = (uint32_t)(gen + 1) & 1u;
            const int need = (h + 1) * NREC + MERGE_LAG;
            {
                const int need2 = min(need, NMAIN + MERGE_LAG_END);
                uint32_t iters = 0;
                while (st->progress < need2) {
                    __nanosleep(200);
                    if (++iters > (1u << 23)) __trap();
                }
            }
            bool poll = need > NMAIN + MERGE_LAG_END;
            for (uint32_t attempt = 0;; attempt++) {
                if (poll) {
                    for (uint32_t iters = 0;; iters++) {
                        const uint4 mu = ld_relaxed4(&g_ml[slot][mi][lane][0]);
                        const uint4 lu = ld_relaxed4(&g_ml[slot][mi][lane][1]);
                        if (!(__reduce_or_sync(0xffffffffu, tagdiff(mu, tb) | tagdiff(lu, tb)) & 1u)) break;
                        if (lane == 0) { PROF_ADD(5, 1); }
                        __nanosleep(100);
                        if (iters > (1u << 21)) __trap();
                    }
                }
                __syncwarp();
                if (lane == 0) {
                    asm volatile("fence.proxy.async.shared::cta;" ::: "memory");
                    mbar_expect_tx(mbar, MBUF_BYTES);
                    bulk_load(mb, &g_po[slot][2 * mi][0][0], 2 * NREC * 512, mbar);
                    bulk_load(mb + 2 * NREC * 512, &g_ml[slot][mi][0][0], NREC * 32, mbar);
                }
                mbar_wait(mbar, mph);
                mph ^= 1u;
                const uint4 mu = lds128(mb + 2 * NREC * 512 + lane * 32), lu = lds128(mb + 2 * NREC * 512 + lane * 32 + 16);
                uint32_t bad = tagdiff(mu, tb) | tagdiff(lu, tb);
                float4 M = make_float4(__uint_as_float(mu.x), __uint_as_float(mu.y), __uint_as_float(mu.z), __uint_as_float(mu.w));
#pragma unroll
                for (int d = 16; d >= 1; d >>= 1) {
                    M.x = fmaxf(M.x, __shfl_xor_sync(0xffffffffu, M.x, d));
                    M.y = fmaxf(M.y, __shfl_xor_sync(0xffffffffu, M.y, d));
                    M.z = fmaxf(M.z, __shfl_xor_sync(0xffffffffu, M.z, d));
                    M.w = fmaxf(M.w, __shfl_xor_sync(0xffffffffu, M.w, d));
                }
                float4 w;
                w.x = ex2((__uint_as_float(mu.x) - M.x) * C); w.y = ex2((__uint_as_float(mu.y) - M.y) * C);
                w.z = ex2((__uint_as_float(mu.z) - M.z) * C); w.w = ex2((__uint_as_float(mu.w) - M.w) * C);
                *(float4*)&st->wbuf[mi][lane][0] = w;
                __syncwarp();
                float4 a0 = make_float4(0.f, 0.f, 0.f, 0.f), a1 = make_float4(0.f, 0.f, 0.f, 0.f);
#pragma unroll 8
                for (int j = 0; j < NREC; j++) {
                    const uint2 ww = lds64(wb + j * 16 + (t & 1) * 8);
                    const uint4 x = lds128(mb + j * 512 + lane * 16), y = lds128(mb + NREC * 512 + j * 512 + lane * 16);
                    const float w0 = __uint_as_float(ww.x), w1 = __uint_as_float(ww.y);
                    bad |= tagdiff(x, tb) | tagdiff(y, tb);
                    a0.x = fmaf(w0, __uint_as_float(x.x), a0.x); a0.y = fmaf(w1, __uint_as_float(x.y), a0.y);
                    a0.z = fmaf(w0, __uint_as_float(x.z), a0.z); a0.w = fmaf(w1, __uint_as_float(x.w), a0.w);
                    a1.x = fmaf(w0, __uint_as_float(y.x), a1.x); a1.y = fmaf(w1, __uint_as_float(y.y), a1.y);
                    a1.z = fmaf(w0, __uint_as_float(y.z), a1.z); a1.w = fmaf(w1, __uint_as_float(y.w), a1.w);
                }
                if (__reduce_or_sync(0xffffffffu, bad) & 1u) {
                    poll = true;
                    if (lane == 0) { PROF_ADD(5, 1000); }
                    if (attempt > (1u << 20)) __trap();
                    continue;
                }
                st_relaxed4(&g_state[h][2 * mi][lane], tagged4(a0.x, a0.y, a0.z, a0.w, 1u));
                st_relaxed4(&g_state[h][2 * mi + 1][lane], tagged4(a1.x, a1.y, a1.z, a1.w, 1u));
                float4 L = make_float4(w.x * __uint_as_float(lu.x), w.y * __uint_as_float(lu.y), w.z * __uint_as_float(lu.z), w.w * __uint_as_float(lu.w));
#pragma unroll
                for (int d = 16; d >= 1; d >>= 1) {
                    L.x += __shfl_xor_sync(0xffffffffu, L.x, d);
                    L.y += __shfl_xor_sync(0xffffffffu, L.y, d);
                    L.z += __shfl_xor_sync(0xffffffffu, L.z, d);
                    L.w += __shfl_xor_sync(0xffffffffu, L.w, d);
                }
                if (lane < 4) {
                    const float4 v = (lane & 1) ? L : M;
                    st_relaxed4(&g_state[h][2 * mi + (lane >> 1)][32 + (lane & 1)], tagged4(v.x, v.y, v.z, v.w, 1u));
                }
                break;
            }
            if (lane < 2) st_relaxed((unsigned int*)&g_merged[slot] + 2 * mi + lane, (unsigned)gen + 1u);
        }
    } else {
        if (lane == 0) {
            PROF_T(0);
            for (int s = 0; s < NST; s++) {
                mbar_init(fullK + s * 8, 1); mbar_init(fullV + s * 8, 5); mbar_init(empty0 + s * 8, 4); mbar_init(pfree0 + s * 8, 4);
            }
            for (int i = 0; i < 2; i++) mbar_init(smem_u32(&st->mfull[i]), 1);
            st->progress = 0;
            asm volatile("fence.mbarrier_init.release.cluster;" ::: "memory");
        }
        __syncwarp();
        asm volatile("bar.arrive 2, %0;" :: "n"(NTHREADS) : "memory");
        if (lane == 0) {
            uint64_t pol;
            asm volatile("createpolicy.fractional.L2::evict_first.b64 %0, 1.0;" : "=l"(pol));
            int s = 0; uint32_t ph = 1;
            int ik = 0, iv = 0;
            auto issueK = [&](uint32_t meta) {
                const uint32_t fb = fullK + ik * 8;
                if (meta & F_STOP) {
                    sts32(meta0 + ik * 4, meta);
                    sts32(meta0 + NST * 4 + ik * 4, 0u);
                    mbar_arrive(fb);
                } else {
                    mbar_wait(empty0 + s * 8, ph);
                    sts32(meta0 + ik * 4, meta);
                    sts32(meta0 + NST * 4 + ik * 4, (uint32_t)s);
                    const int h = meta & 511;
                    mbar_expect_tx(fb, TILE_BYTES + ((meta & F_FIRST) ? Q_BYTES : 0));
                    tma3d(smem_base + s * TILE_BYTES, &mapK, h * SKV + (int)(meta >> 24) * TILE, fb, pol);
                    if (meta & F_FIRST) tma3d_nohint(abase + s * AUX_BYTES, &mapQ, h * SQ, fb);
                    if (++s == NST) { s = 0; ph ^= 1; }
                }
                if (++ik == NST) ik = 0;
            };
            auto issueV = [&](uint32_t meta) {
                mbar_wait(empty0 + s * 8, ph);
                const uint32_t fb = fullV + iv * 8;
                sts32(meta0 + 2 * NST * 4 + iv * 4, (uint32_t)s);
                const int h = meta & 511;
                mbar_expect_tx(fb, TILE_BYTES + ((meta & F_LAST) ? ((meta & F_FIN) ? ST_BYTES : 16) : 0));
                tma3d(smem_base + s * TILE_BYTES, &mapV, h * SKV + (int)(meta >> 24) * TILE, fb, pol);
                if (meta & F_LAST) {
                    if (meta & F_FIN) bulk_load(abase + s * AUX_BYTES, &g_state[h][0][0], ST_BYTES, fb);
                    else              bulk_load(abase + s * AUX_BYTES, &g_merged[h % RG], 16, fb);
                }
                if (++s == NST) { s = 0; ph ^= 1; }
                if (++iv == NST) iv = 0;
            };
            auto first_tile = [&](int u) -> uint32_t {
                if (u >= NTOTAL) return F_STOP;
                if (u >= NMAIN) {
                    const uint32_t h = (uint32_t)(u - NMAIN);
                    return h < (uint32_t)HF2 ? (h | F_FIN | F_FIRST | ((uint32_t)(TPH - 2) << 24))
                                             : (h | F_FIN | F_FIRST | F_LAST | ((uint32_t)(TPH - 1) << 24));
                }
                const uint32_t h = (uint32_t)u >> 5, j = (uint32_t)u & 31u;
                const bool single = j == 31u || (j == 30u && h < (uint32_t)HF2);
                return h | (j << 9) | F_FIRST | (single ? F_LAST : 0u) | (j << 24);
            };
#define CLAIM() atom_inc(&g_ctr, NTOTAL - 1)
            uint32_t cur = first_tile(cta);
            unsigned int claim = 0;
            if (cur & F_LAST) claim = CLAIM();
            issueK(cur);
            while (true) {
                uint32_t nxt;
                if (cur & F_LAST) {
                    const int u = (int)claim + G;
                    st->progress = u;
                    nxt = first_tile(u);
                } else {
                    nxt = ((cur & ~F_FIRST) | F_LAST) + (((cur & F_FIN) ? 1u : 32u) << 24);
                }
                if (nxt & F_LAST) claim = CLAIM();
                issueK(nxt);
                issueV(cur);
                if (nxt & F_STOP) break;
                cur = nxt;
            }
            sts32(meta0 + 2 * NST * 4 + iv * 4, 0u);
            mbar_arrive(fullV + iv * 8);
            PROF_T(2);
        }
    }
}

typedef CUresult (*EncodeFn)(CUtensorMap*, CUtensorMapDataType, cuuint32_t, void*, const cuuint64_t*, const cuuint64_t*,
                             const cuuint32_t*, const cuuint32_t*, CUtensorMapInterleave, CUtensorMapSwizzle,
                             CUtensorMapL2promotion, CUtensorMapFloatOOBfill);

void make_map(EncodeFn enc, CUtensorMap* m, const void* p, int rows, int box_rows) {
    cuuint64_t gd[3] = {64, (cuuint64_t)rows, 2};
    cuuint64_t gs[2] = {256, 128};
    cuuint32_t bd[3] = {64, (cuuint32_t)box_rows, 2};
    cuuint32_t es[3] = {1, 1, 1};
    enc(m, CU_TENSOR_MAP_DATA_TYPE_BFLOAT16, 3, const_cast<void*>(p), gd, gs, bd, es, CU_TENSOR_MAP_INTERLEAVE_NONE,
        CU_TENSOR_MAP_SWIZZLE_128B, CU_TENSOR_MAP_L2_PROMOTION_L2_256B, CU_TENSOR_MAP_FLOAT_OOB_FILL_NONE);
}

}

extern "C" void kernel_launch(void* const* d_in, const int* in_sizes, int n_in, void* d_out, int out_size) {
    (void)in_sizes; (void)n_in; (void)out_size;
    static EncodeFn enc = nullptr;
    static int grid = 0;
    if (!enc) {
        cudaDriverEntryPointQueryResult qr;
        cudaGetDriverEntryPoint("cuTensorMapEncodeTiled", (void**)&enc, cudaEnableDefault, &qr);
        int dev = 0, sms = 0;
        cudaGetDevice(&dev);
        cudaDeviceGetAttribute(&sms, cudaDevAttrMultiProcessorCount, dev);
        grid = sms;
        cudaFuncSetAttribute(attn_kernel, cudaFuncAttributeMaxDynamicSharedMemorySize, SMEM_BYTES);
    }
    CUtensorMap mk, mv, mq;
    make_map(enc, &mq, d_in[0], NH * SQ, SQ);
    make_map(enc, &mk, d_in[1], NH * SKV, TILE);
    make_map(enc, &mv, d_in[2], NH * SKV, TILE);
    attn_kernel<<<grid, NTHREADS, SMEM_BYTES>>>(mk, mv, mq, (__nv_bfloat16*)d_out);
}
```

```cpp
#include <cuda_runtime.h>
#include <cuda_bf16.h>
#include <cuda.h>
#include <stdint.h>

namespace {

constexpr int NH      = 512;
constexpr int SQ      = 4;
constexpr int SKV     = 4096;
constexpr int DH      = 128;
constexpr int TILE    = 64;
constexpr int TPH     = SKV / TILE;
constexpr int NREC    = 32;
constexpr int HF2     = 384;
constexpr int NMAIN   = NH * NREC;
constexpr int NTOTAL  = NMAIN + NH;
constexpr int NST     = 3;
constexpr int TILE_BYTES = TILE * DH * 2;
constexpr int Q_BYTES = SQ * DH * 2;
constexpr int RG      = 64;
constexpr int MERGE_LAG = 600;
static_assert((NH / RG) % 2 == 0, "generation parity must repeat every launch");
static_assert((RG - 1) * NREC >= MERGE_LAG, "a CTA blocked on a ring slot must already have released its own mergers");
static_assert(NST >= 3, "sequence-indexed entries are recycled through the buffer ring");
constexpr int MERGE_LAG_END = 150;
constexpr int ST_WORDS = 144;
constexpr int ST_BYTES = 4 * ST_WORDS * 4;
constexpr int AUX_BYTES = 3072;
static_assert(AUX_BYTES >= ST_BYTES && AUX_BYTES % 1024 == 0, "aux");

constexpr int NTHREADS = 352;

constexpr uint32_t F_FIRST = 1u << 16;
constexpr uint32_t F_LAST  = 1u << 17;
constexpr uint32_t F_FIN   = 1u << 18;
constexpr uint32_t F_STOP  = 1u << 19;
constexpr uint32_t V_END   = 1u << 8;

struct __align__(16) SmemTail {
    uint2    pfrag[NST][4][16];
    float2   xam[NST][4];
    float    xl[NST][4][4];
    float    wmax[2][4][4];
    float    wbuf[2][NREC][4];
    uint64_t full[2][NST];
    uint64_t empty[NST];
    uint64_t mfull[2];
    uint64_t pfree[NST];
    uint32_t meta[NST];
    uint32_t slotK[NST];
    uint32_t slotV[NST];
    uint32_t xmeta[NST];
    volatile int progress;
};
constexpr int MBUF_BYTES = 2 * NREC * 512 + NREC * 32;
constexpr int SMEM_BYTES = 1024 + NST * TILE_BYTES + NST * AUX_BYTES + 2 * MBUF_BYTES + (int)sizeof(SmemTail);

__device__ uint4        g_po[RG][4][NREC][32];
__device__ uint4        g_ml[RG][2][NREC][2];
__device__ uint4        g_state[NH][4][ST_WORDS / 4];
__device__ uint4        g_merged[RG];
__device__ __align__(128) unsigned int g_ctr[32];

__device__ __forceinline__ uint32_t smem_u32(const void* p) { return (uint32_t)__cvta_generic_to_shared(p); }
__device__ __forceinline__ void mbar_init(uint32_t bar, uint32_t cnt) {
    asm volatile("mbarrier.init.shared::cta.b64 [%0], %1;" :: "r"(bar), "r"(cnt));
}
__device__ __forceinline__ void mbar_expect_tx(uint32_t bar, uint32_t bytes) {
    asm volatile("mbarrier.arrive.expect_tx.shared::cta.b64 _, [%0], %1;" :: "r"(bar), "r"(bytes) : "memory");
}
__device__ __forceinline__ void mbar_arrive(uint32_t bar) {
    asm volatile("mbarrier.arrive.shared::cta.b64 _, [%0];" :: "r"(bar) : "memory");
}
__device__ __forceinline__ void mbar_wait(uint32_t bar, uint32_t parity) {
    uint32_t done;
    uint32_t iters = 0;
    do {
        asm volatile("{\n.reg .pred p;\nmbarrier.try_wait.parity.shared::cta.b64 p, [%1], %2;\nselp.u32 %0, 1, 0, p;\n}"
                     : "=r"(done) : "r"(bar), "r"(parity) : "memory");
        if (++iters > (1u << 24)) __trap();
    } while (!done);
}
__device__ __forceinline__ uint32_t tile_off(int row, int chunk) {
    return (uint32_t)((chunk >> 3) * 8192 + row * 128 + (((chunk & 7) ^ (row & 7)) << 4));
}
__device__ __forceinline__ void tma3d(uint32_t dst, const CUtensorMap* m, int row, uint32_t bar, uint64_t pol) {
    asm volatile("cp.async.bulk.tensor.3d.shared::cluster.global.mbarrier::complete_tx::bytes.L2::cache_hint "
                 "[%0], [%1, {%3, %4, %3}], [%2], %5;"
                 :: "r"(dst), "l"(m), "r"(bar), "r"(0), "r"(row), "l"(pol) : "memory");
}
__device__ __forceinline__ void tma3d_nohint(uint32_t dst, const CUtensorMap* m, int row, uint32_t bar) {
    asm volatile("cp.async.bulk.tensor.3d.shared::cluster.global.mbarrier::complete_tx::bytes "
                 "[%0], [%1, {%3, %4, %3}], [%2];"
                 :: "r"(dst), "l"(m), "r"(bar), "r"(0), "r"(row) : "memory");
}
__device__ __forceinline__ void bulk_load(uint32_t dst, const void* src, uint32_t bytes, uint32_t bar) {
    asm volatile("cp.async.bulk.shared::cluster.global.mbarrier::complete_tx::bytes [%0], [%1], %2, [%3];"
                 :: "r"(dst), "l"(src), "r"(bytes), "r"(bar) : "memory");
}
__device__ __forceinline__ void ldsm4(uint32_t* r, uint32_t addr) {
    asm volatile("ldmatrix.sync.aligned.m8n8.x4.shared.b16 {%0,%1,%2,%3}, [%4];"
                 : "=r"(r[0]), "=r"(r[1]), "=r"(r[2]), "=r"(r[3]) : "r"(addr) : "memory");
}
__device__ __forceinline__ void ldsm4t(uint32_t* r, uint32_t addr) {
    asm volatile("ldmatrix.sync.aligned.m8n8.x4.trans.shared.b16 {%0,%1,%2,%3}, [%4];"
                 : "=r"(r[0]), "=r"(r[1]), "=r"(r[2]), "=r"(r[3]) : "r"(addr) : "memory");
}
__device__ __forceinline__ uint32_t lds32(uint32_t a) { uint32_t v; asm volatile("ld.shared.u32 %0, [%1];" : "=r"(v) : "r"(a) : "memory"); return v; }
__device__ __forceinline__ uint2 lds64(uint32_t a) { uint2 v; asm volatile("ld.shared.v2.u32 {%0,%1}, [%2];" : "=r"(v.x), "=r"(v.y) : "r"(a) : "memory"); return v; }
__device__ __forceinline__ uint4 lds128(uint32_t a) { uint4 v; asm volatile("ld.shared.v4.u32 {%0,%1,%2,%3}, [%4];" : "=r"(v.x), "=r"(v.y), "=r"(v.z), "=r"(v.w) : "r"(a) : "memory"); return v; }
__device__ __forceinline__ void sts32(uint32_t a, uint32_t v) { asm volatile("st.shared.u32 [%0], %1;" :: "r"(a), "r"(v) : "memory"); }
__device__ __forceinline__ void sts32_if(bool c, uint32_t a, uint32_t v) {
    asm volatile("{\n.reg .pred p;\nsetp.ne.u32 p, %2, 0;\n@p st.shared.u32 [%0], %1;\n}" :: "r"(a), "r"(v), "r"((uint32_t)c) : "memory");
}
__device__ __forceinline__ void sts64_if(bool c, uint32_t a, uint32_t x, uint32_t y) {
    asm volatile("{\n.reg .pred p;\nsetp.ne.u32 p, %3, 0;\n@p st.shared.v2.u32 [%0], {%1,%2};\n}" :: "r"(a), "r"(x), "r"(y), "r"((uint32_t)c) : "memory");
}
__device__ __forceinline__ void stg16_if(bool c, void* p, uint32_t v) {
    asm volatile("{\n.reg .pred p;\nsetp.ne.u32 p, %2, 0;\n@p st.global.u16 [%0], %1;\n}" :: "l"(p), "h"((unsigned short)v), "r"((uint32_t)c) : "memory");
}
__device__ __forceinline__ void st_relaxed4_if(bool c, void* p, uint4 v) {
    asm volatile("{\n.reg .pred p;\nsetp.ne.u32 p, %5, 0;\n@p st.relaxed.gpu.global.v4.u32 [%0], {%1,%2,%3,%4};\n}"
                 :: "l"(p), "r"(v.x), "r"(v.y), "r"(v.z), "r"(v.w), "r"((uint32_t)c) : "memory");
}
__device__ __forceinline__ void st_relaxed2_if(bool c, void* p, uint32_t x, uint32_t y) {
    asm volatile("{\n.reg .pred p;\nsetp.ne.u32 p, %3, 0;\n@p st.relaxed.gpu.global.v2.u32 [%0], {%1,%2};\n}"
                 :: "l"(p), "r"(x), "r"(y), "r"((uint32_t)c) : "memory");
}
__device__ __forceinline__ void mbar_arrive_if(bool c, uint32_t bar) {
    asm volatile("{\n.reg .pred p;\nsetp.ne.u32 p, %1, 0;\n@p mbarrier.arrive.shared::cta.b64 _, [%0];\n}" :: "r"(bar), "r"((uint32_t)c) : "memory");
}
__device__ __forceinline__ void mma16816(float (&c)[4], uint32_t a0, uint32_t a1, uint32_t a2, uint32_t a3,
                                         uint32_t b0, uint32_t b1) {
    asm volatile("mma.sync.aligned.m16n8k16.row.col.f32.bf16.bf16.f32 {%0,%1,%2,%3}, {%4,%5,%6,%7}, {%8,%9}, {%0,%1,%2,%3};"
                 : "+f"(c[0]), "+f"(c[1]), "+f"(c[2]), "+f"(c[3])
                 : "r"(a0), "r"(a1), "r"(a2), "r"(a3), "r"(b0), "r"(b1));
}
__device__ __forceinline__ uint32_t pack_bf16(float lo, float hi) {
    uint32_t r;
    asm("cvt.rn.bf16x2.f32 %0, %1, %2;" : "=r"(r) : "f"(hi), "f"(lo));
    return r;
}
__device__ __forceinline__ float ex2(float x) {
    float r;
    asm("ex2.approx.ftz.f32 %0, %1;" : "=f"(r) : "f"(x));
    return r;
}
__device__ __forceinline__ float rcp(float x) {
    float r;
    asm("rcp.approx.ftz.f32 %0, %1;" : "=f"(r) : "f"(x));
    return r;
}
__device__ __forceinline__ unsigned int ld_acquire(const unsigned int* p) {
    unsigned int v;
    asm volatile("ld.acquire.gpu.global.u32 %0, [%1];" : "=r"(v) : "l"(p) : "memory");
    return v;
}
__device__ __forceinline__ uint4 ld_relaxed4(const uint4* p) {
    uint4 v;
    asm volatile("ld.relaxed.gpu.global.v4.u32 {%0,%1,%2,%3}, [%4];" : "=r"(v.x), "=r"(v.y), "=r"(v.z), "=r"(v.w) : "l"(p) : "memory");
    return v;
}
__device__ __forceinline__ uint2 ld_relaxed2(const uint2* p) {
    uint2 v;
    asm volatile("ld.relaxed.gpu.global.v2.u32 {%0,%1}, [%2];" : "=r"(v.x), "=r"(v.y) : "l"(p) : "memory");
    return v;
}
__device__ __forceinline__ void st_relaxed4(uint4* p, uint4 v) {
    asm volatile("st.relaxed.gpu.global.v4.u32 [%0], {%1,%2,%3,%4};" :: "l"(p), "r"(v.x), "r"(v.y), "r"(v.z), "r"(v.w) : "memory");
}
__device__ __forceinline__ void st_relaxed(unsigned int* p, unsigned int v) {
    asm volatile("st.relaxed.gpu.global.u32 [%0], %1;" :: "l"(p), "r"(v) : "memory");
}
__device__ __forceinline__ unsigned int atom_inc(unsigned int* p, unsigned int last) {
    unsigned int r;
    asm volatile("atom.relaxed.gpu.global.inc.u32 %0, [%1], %2;" : "=r"(r) : "l"(p), "r"(last) : "memory");
    return r;
}
__device__ __forceinline__ uint32_t tagged(float x, uint32_t tb) { return (__float_as_uint(x) & ~1u) | tb; }
__device__ __forceinline__ uint4 tagged4(float a, float b, float c, float d, uint32_t tb) {
    return make_uint4(tagged(a, tb), tagged(b, tb), tagged(c, tb), tagged(d, tb));
}
__device__ __forceinline__ uint32_t tagdiff(const uint4& v, uint32_t tb) {
    return (v.x ^ tb) | (v.y ^ tb) | (v.z ^ tb) | (v.w ^ tb);
}

#define PIN32(x) asm volatile("" : "+r"(x))
#define PIN64(x) asm volatile("" : "+l"(x))

__global__ void __launch_bounds__(NTHREADS, 1)
attn_kernel(const __grid_constant__ CUtensorMap mapK, const __grid_constant__ CUtensorMap mapV,
            const __grid_constant__ CUtensorMap mapQ, __nv_bfloat16* __restrict__ out)
{
    extern __shared__ unsigned char smem_raw[];
    unsigned char* smem = (unsigned char*)(((uintptr_t)smem_raw + 1023) & ~(uintptr_t)1023);
    unsigned char* aux = smem + NST * TILE_BYTES;
    unsigned char* mbuf = aux + NST * AUX_BYTES;
    SmemTail* st = (SmemTail*)(mbuf + 2 * MBUF_BYTES);

    const int warp = threadIdx.x >> 5;
    const int lane = threadIdx.x & 31;
    const int G = gridDim.x;
    const int cta = blockIdx.x;
    const float C = 0.08838834764831845f * 1.4426950408889634f;
    const uint32_t smem_base = smem_u32(smem);
    const uint32_t abase = smem_u32(aux);
    const uint32_t fullK = smem_u32(&st->full[0][0]), fullV = smem_u32(&st->full[1][0]), empty0 = smem_u32(&st->empty[0]), meta0 = smem_u32(&st->meta[0]);
    const uint32_t pfree0 = smem_u32(&st->pfree[0]), xmeta0 = smem_u32(&st->xmeta[0]);
    const int g = lane >> 2, t = lane & 3;
    const int li = lane >> 3, lr = lane & 7;

    if (warp < 4) {
        const int w = warp;
        uint32_t koff[4];
#pragma unroll
        for (int kp = 0; kp < 4; kp++) koff[kp] = tile_off(16 * w + lr, 4 * kp + li);
        uint32_t qoff[2];
#pragma unroll
        for (int hf = 0; hf < 2; hf++) qoff[hf] = (uint32_t)((hf * 4 + (lr & 3)) * 128);
        const uint32_t qx[2] = {(uint32_t)(lr & 3), (uint32_t)(4 + (lr & 3))};
        uint32_t pf_w = smem_u32(&st->pfrag[0][w][(g & 3) * 4 + t]);
        uint32_t xam_w = smem_u32(&st->xam[0][g & 3]);
        uint32_t xl_w = smem_u32(&st->xl[0][g & 3][w]);
        uint32_t wm_r = smem_u32(&st->wmax[0][g & 3][0]);
        uint32_t k0 = smem_base + koff[0], k1 = smem_base + koff[1];
        uint32_t qo[8];
#pragma unroll
        for (int ks = 0; ks < 8; ks++) {
            qo[ks] = abase + qoff[ks >> 2] + ((((uint32_t)((2 * ks) & 7) + (uint32_t)(li >> 1)) ^ qx[ks >> 2]) << 4);
            PIN32(qo[ks]);
        }
        uint32_t wr_p = g < 4, wr_q = g < 4 && t == 0, wr_a = w == 0 && g < 4 && t == 0, wr_m = threadIdx.x == 31;
        PIN32(pf_w); PIN32(xam_w); PIN32(xl_w); PIN32(wm_r); PIN32(k0); PIN32(k1);
        PIN32(wr_p); PIN32(wr_q); PIN32(wr_a); PIN32(wr_m);

        uint32_t qa[8][4];
        float m = 0.f, l = 0.f;
        int ik = 0; uint32_t ph = 0;
        uint32_t par = 0;
        asm volatile("bar.sync 2, %0;" :: "n"(NTHREADS) : "memory");
        while (true) {
            mbar_wait(pfree0 + ik * 8, ph ^ 1u);
            mbar_wait(fullK + ik * 8, ph);
            const uint32_t meta = lds32(meta0 + ik * 4);
            const uint32_t s = lds32(meta0 + NST * 4 + ik * 4);
            if (meta & F_STOP) break;
            uint32_t kf[8][4];
#pragma unroll
            for (int kp = 0; kp < 4; kp++) {
                ldsm4(kf[2 * kp], ((kp & 1) ? k1 : k0) + s * TILE_BYTES + (kp >> 1) * 8192);
                ldsm4(kf[2 * kp + 1], ((kp & 1) ? k1 : k0) + s * TILE_BYTES + (kp >> 1) * 8192 + 1024);
            }
            if (meta & F_FIRST) {
#pragma unroll
                for (int ks = 0; ks < 8; ks++) ldsm4(qa[ks], qo[ks] + s * AUX_BYTES);
                m = -INFINITY; l = 0.f;
            }
            __syncwarp();
            mbar_arrive_if(lane == 0, empty0 + s * 8);
            float sc[4][4];
#pragma unroll
            for (int i = 0; i < 4; i++) { sc[i][0] = 0.f; sc[i][1] = 0.f; sc[i][2] = 0.f; sc[i][3] = 0.f; }
#pragma unroll
            for (int kp = 0; kp < 4; kp++) {
#pragma unroll
                for (int nt = 0; nt < 2; nt++) {
                    mma16816(sc[nt], qa[2 * kp][0], qa[2 * kp][1], qa[2 * kp][2], qa[2 * kp][3], kf[2 * kp + nt][0], kf[2 * kp + nt][1]);
                    mma16816(sc[2 + nt], qa[2 * kp + 1][0], qa[2 * kp + 1][1], qa[2 * kp + 1][2], qa[2 * kp + 1][3], kf[2 * kp + nt][2], kf[2 * kp + nt][3]);
                }
            }
            const float s0 = sc[0][0] + sc[2][0], s1 = sc[0][1] + sc[2][1], s2 = sc[1][0] + sc[3][0], s3 = sc[1][1] + sc[3][1];
            float mt_ = fmaxf(fmaxf(s0, s1), fmaxf(s2, s3));
            mt_ = fmaxf(mt_, __shfl_xor_sync(0xffffffffu, mt_, 1));
            mt_ = fmaxf(mt_, __shfl_xor_sync(0xffffffffu, mt_, 2));
            sts32_if(wr_q, wm_r + par * 64 + w * 4, __float_as_uint(mt_));
            asm volatile("bar.sync 1, 128;" ::: "memory");
            const uint4 wm = lds128(wm_r + par * 64);
            par ^= 1u;
            const float mn = __uint_as_float(tagged(fmaxf(fmaxf(m, fmaxf(__uint_as_float(wm.x), __uint_as_float(wm.y))),
                                                          fmaxf(__uint_as_float(wm.z), __uint_as_float(wm.w))), (((meta & 511u) / RG) + 1u) & 1u));
            const float mc = -mn * C;
            const float alpha = ex2(fmaf(m, C, mc));
            m = mn;
            const float p0 = ex2(fmaf(s0, C, mc)), p1 = ex2(fmaf(s1, C, mc)), p2 = ex2(fmaf(s2, C, mc)), p3 = ex2(fmaf(s3, C, mc));
            l = fmaf(l, alpha, (p0 + p1) + (p2 + p3));
            float lt = l + __shfl_xor_sync(0xffffffffu, l, 1);
            sts64_if(wr_p, pf_w + ik * 512, pack_bf16(p0, p1), pack_bf16(p2, p3));
            sts64_if(wr_a, xam_w + ik * 32, __float_as_uint(alpha), __float_as_uint(mn));
            sts32_if(wr_m, xmeta0 + ik * 4, meta);
            lt += __shfl_xor_sync(0xffffffffu, lt, 2);
            sts32_if(wr_q, xl_w + ik * 64, __float_as_uint(lt));
            __syncwarp();
            mbar_arrive_if(lane == 0, fullV + ik * 8);
            if (++ik == NST) { ik = 0; ph ^= 1; }
        }
    } else if (warp < 8) {
        const int w = warp - 4;
        uint32_t voff[2];
#pragma unroll
        for (int mt = 0; mt < 2; mt++) voff[mt] = tile_off((li >> 1) * 8 + lr, 4 * w + 2 * mt + (li & 1));
        uint32_t pf_r = smem_u32(&st->pfrag[0][0][(g & 3) * 4 + t]);
        uint32_t xam_r = smem_u32(&st->xam[0][2 * (t & 1)]);
        uint32_t xl_r = smem_u32(&st->xl[0][2 * (t & 1)][0]);
        uint32_t v0 = smem_base + voff[0], v1 = smem_base + voff[1];
        uint32_t a_ml = abase + w * ST_WORDS * 4 + 512 + (t & 1) * 8;
        uint32_t a_so = abase + w * ST_WORDS * 4 + lane * 16;
        uint32_t a_rf = abase + w * 4;
        uint64_t p_out = (uint64_t)(out + 2 * (t & 1) * DH + 32 * w + 16 * (t >> 1) + g);
        uint64_t p_st  = (uint64_t)&g_state[0][w][lane];
        uint64_t p_po  = (uint64_t)&g_po[0][w][0][lane];
        uint64_t p_ml  = (uint64_t)((uint2*)&g_ml[0][w >> 1][0][0] + t);
        uint32_t lo_half = t < 2, ml_writer = g == 0 && !(w & 1);
        PIN32(pf_r); PIN32(xam_r); PIN32(xl_r); PIN32(v0); PIN32(v1); PIN32(a_ml); PIN32(a_so); PIN32(a_rf);
        PIN64(p_out); PIN64(p_st); PIN64(p_po); PIN64(p_ml); PIN32(lo_half); PIN32(ml_writer);

        float acc[2][2][4];
        int iv = 0; uint32_t ph = 0;
        asm volatile("bar.sync 2, %0;" :: "n"(NTHREADS) : "memory");
        while (true) {
            mbar_wait(fullV + iv * 8, ph);
            const uint32_t sv = lds32(meta0 + 2 * NST * 4 + iv * 4);
            const uint32_t s = sv & 0xffu;
            const uint32_t meta = lds32(xmeta0 + iv * 4);
            const uint4 am = lds128(xam_r + iv * 32);
            const uint4 l0 = lds128(xl_r + iv * 64), l1 = lds128(xl_r + iv * 64 + 16);
            uint2 pb[4];
#pragma unroll
            for (int kb = 0; kb < 4; kb++) pb[kb] = lds64(pf_r + iv * 512 + kb * 128);
            uint2 sM = lds64(a_ml + s * AUX_BYTES), sL = lds64(a_ml + s * AUX_BYTES + 16);
            uint4 so = lds128(a_so + s * AUX_BYTES);
            uint32_t ringflag = lds32(a_rf + s * AUX_BYTES);
            uint32_t vf[8][4];
#pragma unroll
            for (int kb = 0; kb < 4; kb++) {
                ldsm4t(vf[2 * kb], v0 + s * TILE_BYTES + kb * 2048);
                ldsm4t(vf[2 * kb + 1], v1 + s * TILE_BYTES + kb * 2048);
            }
            __syncwarp();
            mbar_arrive_if(lane == 0, empty0 + s * 8);
            mbar_arrive_if(lane == 0, pfree0 + iv * 8);
            if (++iv == NST) { iv = 0; ph ^= 1; }
            const bool first = meta & F_FIRST;
            const bool fin = (meta & (F_FIN | F_LAST)) == (F_FIN | F_LAST);
            const bool part = (meta & (F_FIN | F_LAST)) == F_LAST;
            const int h = meta & 511;
            const int slot = h % RG, gen = h / RG;
            const uint32_t jk = (meta >> 9) & 63u;
            const uint32_t tb = (uint32_t)(gen + 1) & 1u;
            unsigned char* op = (unsigned char*)(p_out + (uint32_t)h * (SQ * DH * 2));
            unsigned char* sp = (unsigned char*)(p_st + (uint32_t)h * ST_BYTES);
            unsigned char* pp = (unsigned char*)(p_po + (uint32_t)slot * (4 * NREC * 512) + jk * 512);
            unsigned char* mp = (unsigned char*)(p_ml + (uint32_t)slot * (2 * NREC * 32) + jk * 32);
            const float a0 = __uint_as_float(am.x), a1 = __uint_as_float(am.z);
#pragma unroll
            for (int mt = 0; mt < 2; mt++) {
                acc[0][mt][0] = first ? 0.f : acc[0][mt][0] * a0; acc[0][mt][1] = first ? 0.f : acc[0][mt][1] * a1;
                acc[0][mt][2] = first ? 0.f : acc[0][mt][2] * a0; acc[0][mt][3] = first ? 0.f : acc[0][mt][3] * a1;
                acc[1][mt][0] = 0.f; acc[1][mt][1] = 0.f; acc[1][mt][2] = 0.f; acc[1][mt][3] = 0.f;
            }
            const float M0 = __uint_as_float(am.y), M1 = __uint_as_float(am.w);
            const float L0 = (__uint_as_float(l0.x) + __uint_as_float(l0.y)) + (__uint_as_float(l0.z) + __uint_as_float(l0.w));
            const float L1 = (__uint_as_float(l1.x) + __uint_as_float(l1.y)) + (__uint_as_float(l1.z) + __uint_as_float(l1.w));
            uint32_t ok = fin ? (so.x & so.y & so.z & so.w & sM.x & sM.y & sL.x & sL.y) : (uint32_t)(!part || gen == 0 || ringflag == (uint32_t)gen);
            ok = __reduce_and_sync(0xffffffffu, ok);
            float ca0, ca1, cb0, cb1;
            auto factors = [&]() {
                const float Ms0 = __uint_as_float(sM.x), Ms1 = __uint_as_float(sM.y);
                const float mf0 = fmaxf(Ms0, M0), mf1 = fmaxf(Ms1, M1);
                const float fa0 = ex2((Ms0 - mf0) * C), fb0 = ex2((M0 - mf0) * C);
                const float fa1 = ex2((Ms1 - mf1) * C), fb1 = ex2((M1 - mf1) * C);
                const float inv0 = rcp(fmaf(fa0, __uint_as_float(sL.x), fb0 * L0));
                const float inv1 = rcp(fmaf(fa1, __uint_as_float(sL.y), fb1 * L1));
                ca0 = fa0 * inv0; ca1 = fa1 * inv1; cb0 = fb0 * inv0; cb1 = fb1 * inv1;
            };
            factors();
#pragma unroll
            for (int kb = 0; kb < 4; kb++) {
#pragma unroll
                for (int mt = 0; mt < 2; mt++)
                    mma16816(acc[kb & 1][mt], vf[2 * kb + mt][0], vf[2 * kb + mt][1], vf[2 * kb + mt][2], vf[2 * kb + mt][3], pb[kb].x, pb[kb].y);
            }
            if (!(ok & 1u)) {
                if (fin) {
                    for (uint32_t iters = 0;; iters++) {
                        so = ld_relaxed4(&g_state[h][w][lane]);
                        sM = ld_relaxed2((const uint2*)&g_state[h][w][32] + (t & 1));
                        sL = ld_relaxed2((const uint2*)&g_state[h][w][33] + (t & 1));
                        if (__reduce_and_sync(0xffffffffu, so.x & so.y & so.z & so.w & sM.x & sM.y & sL.x & sL.y) & 1u) break;
                        if (iters > (1u << 22)) __trap();
                    }
                    factors();
                } else {
                    for (uint32_t iters = 0; ld_acquire((const unsigned int*)&g_merged[slot] + w) != (unsigned)gen; iters++) {
                        if (iters > (1u << 24)) __trap();
                    }
                }
            }
#pragma unroll
            for (int mt = 0; mt < 2; mt++) {
#pragma unroll
                for (int i = 0; i < 4; i++) acc[0][mt][i] += acc[1][mt][i];
            }
            float4 o;
            o.x = lo_half ? acc[0][0][0] : acc[0][1][0]; o.y = lo_half ? acc[0][0][1] : acc[0][1][1];
            o.z = lo_half ? acc[0][0][2] : acc[0][1][2]; o.w = lo_half ? acc[0][0][3] : acc[0][1][3];
            {
                const uint32_t r0 = pack_bf16(fmaf(cb0, o.x, ca0 * __uint_as_float(so.x)), fmaf(cb1, o.y, ca1 * __uint_as_float(so.y)));
                const uint32_t r1 = pack_bf16(fmaf(cb0, o.z, ca0 * __uint_as_float(so.z)), fmaf(cb1, o.w, ca1 * __uint_as_float(so.w)));
                stg16_if(fin, op, r0 & 0xffffu);
                stg16_if(fin, op + DH * 2, r0 >> 16);
                stg16_if(fin, op + 16, r1 & 0xffffu);
                stg16_if(fin, op + DH * 2 + 16, r1 >> 16);
                st_relaxed4_if(fin, sp, make_uint4(0, 0, 0, 0));
                st_relaxed4_if(fin && lane < 2, sp + 512, make_uint4(0, 0, 0, 0));
            }
            {
                st_relaxed4_if(part, pp, tagged4(o.x, o.y, o.z, o.w, tb));
                st_relaxed2_if(part && ml_writer, mp, tagged(lo_half ? M0 : L0, tb), tagged(lo_half ? M1 : L1, tb));
            }
            if (sv & V_END) break;
        }
    } else if (warp < 10) {
        asm volatile("bar.sync 2, %0;" :: "n"(NTHREADS) : "memory");
        const int mi = warp - 8;
        const uint32_t mb = smem_u32(mbuf) + mi * MBUF_BYTES;
        const uint32_t mbar = smem_u32(&st->mfull[mi]);
        const uint32_t wb = smem_u32(&st->wbuf[mi][0][0]);
        uint32_t mph = 0;
        for (int h = cta; h < NH; h += G) {
            const int slot = h % RG, gen = h / RG;
            const uint32_t tb = (uint32_t)(gen + 1) & 1u;
            const int need = (h + 1) * NREC + MERGE_LAG;
            {
                const int need2 = min(need, NMAIN + MERGE_LAG_END);
                uint32_t iters = 0;
                while (st->progress < need2) {
                    __nanosleep(200);
                    if (++iters > (1u << 23)) __trap();
                }
            }
            bool poll = need > NMAIN + MERGE_LAG_END;
            for (uint32_t attempt = 0;; attempt++) {
                if (poll) {
                    for (uint32_t iters = 0;; iters++) {
                        const uint4 mu = ld_relaxed4(&g_ml[slot][mi][lane][0]);
                        const uint4 lu = ld_relaxed4(&g_ml[slot][mi][lane][1]);
                        if (!(__reduce_or_sync(0xffffffffu, tagdiff(mu, tb) | tagdiff(lu, tb)) & 1u)) break;
                        __nanosleep(100);
                        if (iters > (1u << 21)) __trap();
                    }
                }
                __syncwarp();
                if (lane == 0) {
                    asm volatile("fence.proxy.async.shared::cta;" ::: "memory");
                    mbar_expect_tx(mbar, MBUF_BYTES);
                    bulk_load(mb, &g_po[slot][2 * mi][0][0], 2 * NREC * 512, mbar);
                    bulk_load(mb + 2 * NREC * 512, &g_ml[slot][mi][0][0], NREC * 32, mbar);
                }
                mbar_wait(mbar, mph);
                mph ^= 1u;
                const uint4 mu = lds128(mb + 2 * NREC * 512 + lane * 32), lu = lds128(mb + 2 * NREC * 512 + lane * 32 + 16);
                uint32_t bad = tagdiff(mu, tb) | tagdiff(lu, tb);
                float4 M = make_float4(__uint_as_float(mu.x), __uint_as_float(mu.y), __uint_as_float(mu.z), __uint_as_float(mu.w));
#pragma unroll
                for (int d = 16; d >= 1; d >>= 1) {
                    M.x = fmaxf(M.x, __shfl_xor_sync(0xffffffffu, M.x, d));
                    M.y = fmaxf(M.y, __shfl_xor_sync(0xffffffffu, M.y, d));
                    M.z = fmaxf(M.z, __shfl_xor_sync(0xffffffffu, M.z, d));
                    M.w = fmaxf(M.w, __shfl_xor_sync(0xffffffffu, M.w, d));
                }
                M.x = __uint_as_float(tagged(M.x, 1u)); M.y = __uint_as_float(tagged(M.y, 1u));
                M.z = __uint_as_float(tagged(M.z, 1u)); M.w = __uint_as_float(tagged(M.w, 1u));
                float4 w;
                w.x = ex2((__uint_as_float(mu.x) - M.x) * C); w.y = ex2((__uint_as_float(mu.y) - M.y) * C);
                w.z = ex2((__uint_as_float(mu.z) - M.z) * C); w.w = ex2((__uint_as_float(mu.w) - M.w) * C);
                *(float4*)&st->wbuf[mi][lane][0] = w;
                __syncwarp();
                float4 a0 = make_float4(0.f, 0.f, 0.f, 0.f), a1 = make_float4(0.f, 0.f, 0.f, 0.f);
#pragma unroll 8
                for (int j = 0; j < NREC; j++) {
                    const uint2 ww = lds64(wb + j * 16 + (t & 1) * 8);
                    const uint4 x = lds128(mb + j * 512 + lane * 16), y = lds128(mb + NREC * 512 + j * 512 + lane * 16);
                    const float w0 = __uint_as_float(ww.x), w1 = __uint_as_float(ww.y);
                    bad |= tagdiff(x, tb) | tagdiff(y, tb);
                    a0.x = fmaf(w0, __uint_as_float(x.x), a0.x); a0.y = fmaf(w1, __uint_as_float(x.y), a0.y);
                    a0.z = fmaf(w0, __uint_as_float(x.z), a0.z); a0.w = fmaf(w1, __uint_as_float(x.w), a0.w);
                    a1.x = fmaf(w0, __uint_as_float(y.x), a1.x); a1.y = fmaf(w1, __uint_as_float(y.y), a1.y);
                    a1.z = fmaf(w0, __uint_as_float(y.z), a1.z); a1.w = fmaf(w1, __uint_as_float(y.w), a1.w);
                }
                if (__reduce_or_sync(0xffffffffu, bad) & 1u) {
                    poll = true;
                    if (attempt > (1u << 20)) __trap();
                    continue;
                }
                st_relaxed4(&g_state[h][2 * mi][lane], tagged4(a0.x, a0.y, a0.z, a0.w, 1u));
                st_relaxed4(&g_state[h][2 * mi + 1][lane], tagged4(a1.x, a1.y, a1.z, a1.w, 1u));
                float4 L = make_float4(w.x * __uint_as_float(lu.x), w.y * __uint_as_float(lu.y), w.z * __uint_as_float(lu.z), w.w * __uint_as_float(lu.w));
#pragma unroll
                for (int d = 16; d >= 1; d >>= 1) {
                    L.x += __shfl_xor_sync(0xffffffffu, L.x, d);
                    L.y += __shfl_xor_sync(0xffffffffu, L.y, d);
                    L.z += __shfl_xor_sync(0xffffffffu, L.z, d);
                    L.w += __shfl_xor_sync(0xffffffffu, L.w, d);
                }
                if (lane < 4) {
                    const float4 v = (lane & 1) ? L : M;
                    st_relaxed4(&g_state[h][2 * mi + (lane >> 1)][32 + (lane & 1)], tagged4(v.x, v.y, v.z, v.w, 1u));
                }
                break;
            }
            if (lane < 2) st_relaxed((unsigned int*)&g_merged[slot] + 2 * mi + lane, (unsigned)gen + 1u);
        }
    } else {
        if (lane == 0) {
            for (int s = 0; s < NST; s++) {
                mbar_init(fullK + s * 8, 1); mbar_init(fullV + s * 8, 5); mbar_init(empty0 + s * 8, 4); mbar_init(pfree0 + s * 8, 4);
            }
            for (int i = 0; i < 2; i++) mbar_init(smem_u32(&st->mfull[i]), 1);
            st->progress = 0;
            asm volatile("fence.mbarrier_init.release.cluster;" ::: "memory");
        }
        __syncwarp();
        asm volatile("bar.arrive 2, %0;" :: "n"(NTHREADS) : "memory");
        if (lane == 0) {
            uint64_t pol;
            asm volatile("createpolicy.fractional.L2::evict_first.b64 %0, 1.0;" : "=l"(pol));
            int s = 0; uint32_t ph = 1;
            int ik = 0, iv = 0;
            auto issueK = [&](uint32_t meta) {
                const uint32_t fb = fullK + ik * 8;
                if (meta & F_STOP) {
                    sts32(meta0 + ik * 4, meta);
                    mbar_arrive(fb);
                } else {
                    mbar_wait(empty0 + s * 8, ph);
                    sts32(meta0 + ik * 4, meta);
                    sts32(meta0 + NST * 4 + ik * 4, (uint32_t)s);
                    const int h = meta & 511;
                    mbar_expect_tx(fb, TILE_BYTES + ((meta & F_FIRST) ? Q_BYTES : 0));
                    tma3d(smem_base + s * TILE_BYTES, &mapK, h * SKV + (int)(meta >> 24) * TILE, fb, pol);
                    if (meta & F_FIRST) tma3d_nohint(abase + s * AUX_BYTES, &mapQ, h * SQ, fb);
                    if (++s == NST) { s = 0; ph ^= 1; }
                }
                if (++ik == NST) ik = 0;
            };
            auto issueV = [&](uint32_t meta, bool end) {
                mbar_wait(empty0 + s * 8, ph);
                const uint32_t fb = fullV + iv * 8;
                sts32(meta0 + 2 * NST * 4 + iv * 4, (uint32_t)s | (end ? V_END : 0u));
                const int h = meta & 511;
                const bool fin = (meta & (F_FIN | F_LAST)) == (F_FIN | F_LAST);
                const bool flag = (meta & (F_FIN | F_LAST)) == F_LAST && h >= RG;
                mbar_expect_tx(fb, TILE_BYTES + (fin ? ST_BYTES : 0) + (flag ? 16 : 0));
                tma3d(smem_base + s * TILE_BYTES, &mapV, h * SKV + (int)(meta >> 24) * TILE, fb, pol);
                if (fin)  bulk_load(abase + s * AUX_BYTES, &g_state[h][0][0], ST_BYTES, fb);
                if (flag) bulk_load(abase + s * AUX_BYTES, &g_merged[h % RG], 16, fb);
                if (++s == NST) { s = 0; ph ^= 1; }
                if (++iv == NST) iv = 0;
            };
            auto first_tile = [&](int u) -> uint32_t {
                if (u >= NTOTAL) return F_STOP;
                if (u >= NMAIN) {
                    const uint32_t h = (uint32_t)(u - NMAIN);
                    return h < (uint32_t)HF2 ? (h | F_FIN | F_FIRST | ((uint32_t)(TPH - 2) << 24))
                                             : (h | F_FIN | F_FIRST | F_LAST | ((uint32_t)(TPH - 1) << 24));
                }
                const uint32_t h = (uint32_t)u >> 5, j = (uint32_t)u & 31u;
                const bool single = j == 31u || (j == 30u && h < (uint32_t)HF2);
                return h | (j << 9) | F_FIRST | (single ? F_LAST : 0u) | (j << 24);
            };
            uint32_t cur = first_tile(cta);
            unsigned int claim = 0;
            if (cur & F_LAST) claim = atom_inc(&g_ctr[0], NTOTAL - 1);
            issueK(cur);
            while (true) {
                uint32_t nxt;
                if (cur & F_LAST) {
                    const int u = (int)claim + G;
                    st->progress = u;
                    nxt = first_tile(u);
                } else {
                    nxt = ((cur & ~F_FIRST) | F_LAST) + (((cur & F_FIN) ? 1u : 32u) << 24);
                }
                if (nxt & F_LAST) claim = atom_inc(&g_ctr[0], NTOTAL - 1);
                issueK(nxt);
                issueV(cur, (nxt & F_STOP) != 0u);
                if (nxt & F_STOP) break;
                cur = nxt;
            }
        }
    }
}

typedef CUresult (*EncodeFn)(CUtensorMap*, CUtensorMapDataType, cuuint32_t, void*, const cuuint64_t*, const cuuint64_t*,
                             const cuuint32_t*, const cuuint32_t*, CUtensorMapInterleave, CUtensorMapSwizzle,
                             CUtensorMapL2promotion, CUtensorMapFloatOOBfill);

void make_map(EncodeFn enc, CUtensorMap* m, const void* p, int rows, int box_rows) {
    cuuint64_t gd[3] = {64, (cuuint64_t)rows, 2};
    cuuint64_t gs[2] = {256, 128};
    cuuint32_t bd[3] = {64, (cuuint32_t)box_rows, 2};
    cuuint32_t es[3] = {1, 1, 1};
    enc(m, CU_TENSOR_MAP_DATA_TYPE_BFLOAT16, 3, const_cast<void*>(p), gd, gs, bd, es, CU_TENSOR_MAP_INTERLEAVE_NONE,
        CU_TENSOR_MAP_SWIZZLE_128B, CU_TENSOR_MAP_L2_PROMOTION_L2_256B, CU_TENSOR_MAP_FLOAT_OOB_FILL_NONE);
}

}

extern "C" void kernel_launch(void* const* d_in, const int* in_sizes, int n_in, void* d_out, int out_size) {
    (void)in_sizes; (void)n_in; (void)out_size;
    static EncodeFn enc = nullptr;
    static int grid = 0;
    if (!enc) {
        cudaDriverEntryPointQueryResult qr;
        cudaGetDriverEntryPoint("cuTensorMapEncodeTiled", (void**)&enc, cudaEnableDefault, &qr);
        int dev = 0, sms = 0;
        cudaGetDevice(&dev);
        cudaDeviceGetAttribute(&sms, cudaDevAttrMultiProcessorCount, dev);
        grid = sms;
        cudaFuncSetAttribute(attn_kernel, cudaFuncAttributeMaxDynamicSharedMemorySize, SMEM_BYTES);
    }
    CUtensorMap mk, mv, mq;
    make_map(enc, &mq, d_in[0], NH * SQ, SQ);
    make_map(enc, &mk, d_in[1], NH * SKV, TILE);
    make_map(enc, &mv, d_in[2], NH * SKV, TILE);
    attn_kernel<<<grid, NTHREADS, SMEM_BYTES>>>(mk, mv, mq, (__nv_bfloat16*)d_out);
}
```

```cpp
#include <cuda_runtime.h>
#include <cuda_bf16.h>
#include <cuda.h>
#include <stdint.h>

namespace {

constexpr int NH      = 512;
constexpr int SQ      = 4;
constexpr int SKV     = 4096;
constexpr int DH      = 128;
constexpr int TILE    = 64;
constexpr int TPH     = SKV / TILE;
constexpr int NREC    = TPH - 2;
constexpr int NRECP   = 64;
constexpr int RECB    = 256;
constexpr int NMAIN   = NH * NREC;
constexpr int NTOTAL  = NMAIN + NH;
constexpr int NST     = 3;
constexpr int TILE_BYTES = TILE * DH * 2;
constexpr int Q_BYTES = SQ * DH * 2;
constexpr int RG      = 64;
constexpr int MERGE_LAG = 700;
static_assert((NH / RG) % 2 == 0, "generation parity must repeat every launch");
static_assert((RG - 1) * NREC >= MERGE_LAG, "a CTA blocked on a ring slot must already have released its own mergers");
static_assert(NST >= 3, "sequence-indexed entries are recycled through the buffer ring");
constexpr int MERGE_LAG_END = 100;
constexpr int ST_WORDS = 144;
constexpr int ST_BYTES = 4 * ST_WORDS * 4;
constexpr int AUX_BYTES = 3072;
static_assert(AUX_BYTES >= ST_BYTES && AUX_BYTES % 1024 == 0, "aux");

constexpr int NTHREADS = 352;

constexpr uint32_t F_FIRST = 1u << 16;
constexpr uint32_t F_LAST  = 1u << 17;
constexpr uint32_t F_FIN   = 1u << 18;
constexpr uint32_t F_STOP  = 1u << 19;
constexpr uint32_t V_END   = 1u << 8;

struct __align__(16) SmemTail {
    uint2    pfrag[NST][4][16];
    float2   xam[NST][4];
    float    xl[NST][4][4];
    float    wmax[2][4][4];
    float    wbuf[2][NRECP][4];
    uint64_t full[2][NST];
    uint64_t empty[NST];
    uint64_t mfull[2];
    uint64_t pfree[NST];
    uint32_t meta[NST];
    uint32_t slotK[NST];
    uint32_t slotV[NST];
    uint32_t xmeta[NST];
    volatile int progress;
};
constexpr int MBUF_BYTES = 2 * NRECP * RECB + NRECP * 32;
constexpr int SMEM_BYTES = 1024 + NST * TILE_BYTES + NST * AUX_BYTES + 2 * MBUF_BYTES + (int)sizeof(SmemTail);

__device__ uint4        g_po[RG][4][NRECP][RECB / 16];
__device__ uint4        g_ml[RG][2][NRECP][2];
__device__ uint4        g_state[NH][4][ST_WORDS / 4];
__device__ uint4        g_merged[RG];
__device__ __align__(128) unsigned int g_ctr[32];

__device__ __forceinline__ uint32_t smem_u32(const void* p) { return (uint32_t)__cvta_generic_to_shared(p); }
__device__ __forceinline__ void mbar_init(uint32_t bar, uint32_t cnt) {
    asm volatile("mbarrier.init.shared::cta.b64 [%0], %1;" :: "r"(bar), "r"(cnt));
}
__device__ __forceinline__ void mbar_expect_tx(uint32_t bar, uint32_t bytes) {
    asm volatile("mbarrier.arrive.expect_tx.shared::cta.b64 _, [%0], %1;" :: "r"(bar), "r"(bytes) : "memory");
}
__device__ __forceinline__ void mbar_arrive(uint32_t bar) {
    asm volatile("mbarrier.arrive.shared::cta.b64 _, [%0];" :: "r"(bar) : "memory");
}
__device__ __forceinline__ void mbar_wait(uint32_t bar, uint32_t parity) {
    uint32_t done;
    uint32_t iters = 0;
    do {
        asm volatile("{\n.reg .pred p;\nmbarrier.try_wait.parity.shared::cta.b64 p, [%1], %2;\nselp.u32 %0, 1, 0, p;\n}"
                     : "=r"(done) : "r"(bar), "r"(parity) : "memory");
        if (++iters > (1u << 24)) __trap();
    } while (!done);
}
__device__ __forceinline__ uint32_t tile_off(int row, int chunk) {
    return (uint32_t)((chunk >> 3) * 8192 + row * 128 + (((chunk & 7) ^ (row & 7)) << 4));
}
__device__ __forceinline__ void tma3d(uint32_t dst, const CUtensorMap* m, int row, uint32_t bar, uint64_t pol) {
    asm volatile("cp.async.bulk.tensor.3d.shared::cluster.global.mbarrier::complete_tx::bytes.L2::cache_hint "
                 "[%0], [%1, {%3, %4, %3}], [%2], %5;"
                 :: "r"(dst), "l"(m), "r"(bar), "r"(0), "r"(row), "l"(pol) : "memory");
}
__device__ __forceinline__ void tma3d_nohint(uint32_t dst, const CUtensorMap* m, int row, uint32_t bar) {
    asm volatile("cp.async.bulk.tensor.3d.shared::cluster.global.mbarrier::complete_tx::bytes "
                 "[%0], [%1, {%3, %4, %3}], [%2];"
                 :: "r"(dst), "l"(m), "r"(bar), "r"(0), "r"(row) : "memory");
}
__device__ __forceinline__ void bulk_load(uint32_t dst, const void* src, uint32_t bytes, uint32_t bar) {
    asm volatile("cp.async.bulk.shared::cluster.global.mbarrier::complete_tx::bytes [%0], [%1], %2, [%3];"
                 :: "r"(dst), "l"(src), "r"(bytes), "r"(bar) : "memory");
}
__device__ __forceinline__ void ldsm4(uint32_t* r, uint32_t addr) {
    asm volatile("ldmatrix.sync.aligned.m8n8.x4.shared.b16 {%0,%1,%2,%3}, [%4];"
                 : "=r"(r[0]), "=r"(r[1]), "=r"(r[2]), "=r"(r[3]) : "r"(addr) : "memory");
}
__device__ __forceinline__ void ldsm4t(uint32_t* r, uint32_t addr) {
    asm volatile("ldmatrix.sync.aligned.m8n8.x4.trans.shared.b16 {%0,%1,%2,%3}, [%4];"
                 : "=r"(r[0]), "=r"(r[1]), "=r"(r[2]), "=r"(r[3]) : "r"(addr) : "memory");
}
__device__ __forceinline__ uint32_t lds32(uint32_t a) { uint32_t v; asm volatile("ld.shared.u32 %0, [%1];" : "=r"(v) : "r"(a) : "memory"); return v; }
__device__ __forceinline__ uint2 lds64(uint32_t a) { uint2 v; asm volatile("ld.shared.v2.u32 {%0,%1}, [%2];" : "=r"(v.x), "=r"(v.y) : "r"(a) : "memory"); return v; }
__device__ __forceinline__ uint4 lds128(uint32_t a) { uint4 v; asm volatile("ld.shared.v4.u32 {%0,%1,%2,%3}, [%4];" : "=r"(v.x), "=r"(v.y), "=r"(v.z), "=r"(v.w) : "r"(a) : "memory"); return v; }
__device__ __forceinline__ void sts32(uint32_t a, uint32_t v) { asm volatile("st.shared.u32 [%0], %1;" :: "r"(a), "r"(v) : "memory"); }
__device__ __forceinline__ void sts32_if(bool c, uint32_t a, uint32_t v) {
    asm volatile("{\n.reg .pred p;\nsetp.ne.u32 p, %2, 0;\n@p st.shared.u32 [%0], %1;\n}" :: "r"(a), "r"(v), "r"((uint32_t)c) : "memory");
}
__device__ __forceinline__ void sts64_if(bool c, uint32_t a, uint32_t x, uint32_t y) {
    asm volatile("{\n.reg .pred p;\nsetp.ne.u32 p, %3, 0;\n@p st.shared.v2.u32 [%0], {%1,%2};\n}" :: "r"(a), "r"(x), "r"(y), "r"((uint32_t)c) : "memory");
}
__device__ __forceinline__ void stg16_if(bool c, void* p, uint32_t v) {
    asm volatile("{\n.reg .pred p;\nsetp.ne.u32 p, %2, 0;\n@p st.global.u16 [%0], %1;\n}" :: "l"(p), "h"((unsigned short)v), "r"((uint32_t)c) : "memory");
}
__device__ __forceinline__ void st_relaxed4_if(bool c, void* p, uint4 v) {
    asm volatile("{\n.reg .pred p;\nsetp.ne.u32 p, %5, 0;\n@p st.relaxed.gpu.global.v4.u32 [%0], {%1,%2,%3,%4};\n}"
                 :: "l"(p), "r"(v.x), "r"(v.y), "r"(v.z), "r"(v.w), "r"((uint32_t)c) : "memory");
}
__device__ __forceinline__ void st_relaxed2_if(bool c, void* p, uint32_t x, uint32_t y) {
    asm volatile("{\n.reg .pred p;\nsetp.ne.u32 p, %3, 0;\n@p st.relaxed.gpu.global.v2.u32 [%0], {%1,%2};\n}"
                 :: "l"(p), "r"(x), "r"(y), "r"((uint32_t)c) : "memory");
}
__device__ __forceinline__ void mbar_arrive_if(bool c, uint32_t bar) {
    asm volatile("{\n.reg .pred p;\nsetp.ne.u32 p, %1, 0;\n@p mbarrier.arrive.shared::cta.b64 _, [%0];\n}" :: "r"(bar), "r"((uint32_t)c) : "memory");
}
__device__ __forceinline__ void mma16816(float (&c)[4], uint32_t a0, uint32_t a1, uint32_t a2, uint32_t a3,
                                         uint32_t b0, uint32_t b1) {
    asm volatile("mma.sync.aligned.m16n8k16.row.col.f32.bf16.bf16.f32 {%0,%1,%2,%3}, {%4,%5,%6,%7}, {%8,%9}, {%0,%1,%2,%3};"
                 : "+f"(c[0]), "+f"(c[1]), "+f"(c[2]), "+f"(c[3])
                 : "r"(a0), "r"(a1), "r"(a2), "r"(a3), "r"(b0), "r"(b1));
}
__device__ __forceinline__ uint32_t pack_bf16(float lo, float hi) {
    uint32_t r;
    asm("cvt.rn.bf16x2.f32 %0, %1, %2;" : "=r"(r) : "f"(hi), "f"(lo));
    return r;
}
__device__ __forceinline__ float ex2(float x) {
    float r;
    asm("ex2.approx.ftz.f32 %0, %1;" : "=f"(r) : "f"(x));
    return r;
}
__device__ __forceinline__ float rcp(float x) {
    float r;
    asm("rcp.approx.ftz.f32 %0, %1;" : "=f"(r) : "f"(x));
    return r;
}
__device__ __forceinline__ unsigned int ld_acquire(const unsigned int* p) {
    unsigned int v;
    asm volatile("ld.acquire.gpu.global.u32 %0, [%1];" : "=r"(v) : "l"(p) : "memory");
    return v;
}
__device__ __forceinline__ uint4 ld_relaxed4(const uint4* p) {
    uint4 v;
    asm volatile("ld.relaxed.gpu.global.v4.u32 {%0,%1,%2,%3}, [%4];" : "=r"(v.x), "=r"(v.y), "=r"(v.z), "=r"(v.w) : "l"(p) : "memory");
    return v;
}
__device__ __forceinline__ uint2 ld_relaxed2(const uint2* p) {
    uint2 v;
    asm volatile("ld.relaxed.gpu.global.v2.u32 {%0,%1}, [%2];" : "=r"(v.x), "=r"(v.y) : "l"(p) : "memory");
    return v;
}
__device__ __forceinline__ void st_relaxed4(uint4* p, uint4 v) {
    asm volatile("st.relaxed.gpu.global.v4.u32 [%0], {%1,%2,%3,%4};" :: "l"(p), "r"(v.x), "r"(v.y), "r"(v.z), "r"(v.w) : "memory");
}
__device__ __forceinline__ void st_relaxed(unsigned int* p, unsigned int v) {
    asm volatile("st.relaxed.gpu.global.u32 [%0], %1;" :: "l"(p), "r"(v) : "memory");
}
__device__ __forceinline__ unsigned int atom_inc(unsigned int* p, unsigned int last) {
    unsigned int r;
    asm volatile("atom.relaxed.gpu.global.inc.u32 %0, [%1], %2;" : "=r"(r) : "l"(p), "r"(last) : "memory");
    return r;
}
__device__ __forceinline__ uint32_t tagged(float x, uint32_t tb) { return (__float_as_uint(x) & ~1u) | tb; }
__device__ __forceinline__ uint4 tagged4(float a, float b, float c, float d, uint32_t tb) {
    return make_uint4(tagged(a, tb), tagged(b, tb), tagged(c, tb), tagged(d, tb));
}
__device__ __forceinline__ uint32_t pack_tag(float lo, float hi, uint32_t tb) {
    const uint32_t l = (((__float_as_uint(lo) + 0x10000u - (tb << 16)) >> 17) << 1) | tb;
    return (pack_bf16(0.f, hi) & 0xffff0000u) | (l & 0xffffu);
}
__device__ __forceinline__ uint32_t tagdiff(const uint4& v, uint32_t tb) {
    return (v.x ^ tb) | (v.y ^ tb) | (v.z ^ tb) | (v.w ^ tb);
}

#define PIN32(x) asm volatile("" : "+r"(x))
#define PIN64(x) asm volatile("" : "+l"(x))

__global__ void __launch_bounds__(NTHREADS, 1)
attn_kernel(const __grid_constant__ CUtensorMap mapK, const __grid_constant__ CUtensorMap mapV,
            const __grid_constant__ CUtensorMap mapQ, __nv_bfloat16* __restrict__ out)
{
    extern __shared__ unsigned char smem_raw[];
    unsigned char* smem = (unsigned char*)(((uintptr_t)smem_raw + 1023) & ~(uintptr_t)1023);
    unsigned char* aux = smem + NST * TILE_BYTES;
    unsigned char* mbuf = aux + NST * AUX_BYTES;
    SmemTail* st = (SmemTail*)(mbuf + 2 * MBUF_BYTES);

    const int warp = threadIdx.x >> 5;
    const int lane = threadIdx.x & 31;
    const int G = gridDim.x;
    const int cta = blockIdx.x;
    const float C = 0.08838834764831845f * 1.4426950408889634f;
    const uint32_t smem_base = smem_u32(smem);
    const uint32_t abase = smem_u32(aux);
    const uint32_t fullK = smem_u32(&st->full[0][0]), fullV = smem_u32(&st->full[1][0]), empty0 = smem_u32(&st->empty[0]), meta0 = smem_u32(&st->meta[0]);
    const uint32_t pfree0 = smem_u32(&st->pfree[0]), xmeta0 = smem_u32(&st->xmeta[0]);
    const int g = lane >> 2, t = lane & 3;
    const int li = lane >> 3, lr = lane & 7;

    if (warp < 4) {
        const int w = warp;
        uint32_t koff[4];
#pragma unroll
        for (int kp = 0; kp < 4; kp++) koff[kp] = tile_off(16 * w + lr, 4 * kp + li);
        uint32_t qoff[2];
#pragma unroll
        for (int hf = 0; hf < 2; hf++) qoff[hf] = (uint32_t)((hf * 4 + (lr & 3)) * 128);
        const uint32_t qx[2] = {(uint32_t)(lr & 3), (uint32_t)(4 + (lr & 3))};
        uint32_t pf_w = smem_u32(&st->pfrag[0][w][(g & 3) * 4 + t]);
        uint32_t xam_w = smem_u32(&st->xam[0][g & 3]);
        uint32_t xl_w = smem_u32(&st->xl[0][g & 3][w]);
        uint32_t wm_r = smem_u32(&st->wmax[0][g & 3][0]);
        uint32_t k0 = smem_base + koff[0], k1 = smem_base + koff[1];
        uint32_t qo[8];
#pragma unroll
        for (int ks = 0; ks < 8; ks++) {
            qo[ks] = abase + qoff[ks >> 2] + ((((uint32_t)((2 * ks) & 7) + (uint32_t)(li >> 1)) ^ qx[ks >> 2]) << 4);
            PIN32(qo[ks]);
        }
        uint32_t wr_p = g < 4, wr_q = g < 4 && t == 0, wr_a = w == 0 && g < 4 && t == 0, wr_m = threadIdx.x == 31;
        PIN32(pf_w); PIN32(xam_w); PIN32(xl_w); PIN32(wm_r); PIN32(k0); PIN32(k1);
        PIN32(wr_p); PIN32(wr_q); PIN32(wr_a); PIN32(wr_m);

        uint32_t qa[8][4];
        float m = 0.f, l = 0.f;
        int ik = 0; uint32_t ph = 0;
        uint32_t par = 0;
        asm volatile("bar.sync 2, %0;" :: "n"(NTHREADS) : "memory");
        while (true) {
            mbar_wait(pfree0 + ik * 8, ph ^ 1u);
            mbar_wait(fullK + ik * 8, ph);
            const uint32_t meta = lds32(meta0 + ik * 4);
            const uint32_t s = lds32(meta0 + NST * 4 + ik * 4);
            if (meta & F_STOP) break;
            uint32_t kf[8][4];
#pragma unroll
            for (int kp = 0; kp < 4; kp++) {
                ldsm4(kf[2 * kp], ((kp & 1) ? k1 : k0) + s * TILE_BYTES + (kp >> 1) * 8192);
                ldsm4(kf[2 * kp + 1], ((kp & 1) ? k1 : k0) + s * TILE_BYTES + (kp >> 1) * 8192 + 1024);
            }
            if (meta & F_FIRST) {
#pragma unroll
                for (int ks = 0; ks < 8; ks++) ldsm4(qa[ks], qo[ks] + s * AUX_BYTES);
                m = -INFINITY; l = 0.f;
            }
            __syncwarp();
            mbar_arrive_if(lane == 0, empty0 + s * 8);
            float sc[4][4];
#pragma unroll
            for (int i = 0; i < 4; i++) { sc[i][0] = 0.f; sc[i][1] = 0.f; sc[i][2] = 0.f; sc[i][3] = 0.f; }
#pragma unroll
            for (int kp = 0; kp < 4; kp++) {
#pragma unroll
                for (int nt = 0; nt < 2; nt++) {
                    mma16816(sc[nt], qa[2 * kp][0], qa[2 * kp][1], qa[2 * kp][2], qa[2 * kp][3], kf[2 * kp + nt][0], kf[2 * kp + nt][1]);
                    mma16816(sc[2 + nt], qa[2 * kp + 1][0], qa[2 * kp + 1][1], qa[2 * kp + 1][2], qa[2 * kp + 1][3], kf[2 * kp + nt][2], kf[2 * kp + nt][3]);
                }
            }
            const float s0 = sc[0][0] + sc[2][0], s1 = sc[0][1] + sc[2][1], s2 = sc[1][0] + sc[3][0], s3 = sc[1][1] + sc[3][1];
            float mt_ = fmaxf(fmaxf(s0, s1), fmaxf(s2, s3));
            mt_ = fmaxf(mt_, __shfl_xor_sync(0xffffffffu, mt_, 1));
            mt_ = fmaxf(mt_, __shfl_xor_sync(0xffffffffu, mt_, 2));
            sts32_if(wr_q, wm_r + par * 64 + w * 4, __float_as_uint(mt_));
            asm volatile("bar.sync 1, 128;" ::: "memory");
            const uint4 wm = lds128(wm_r + par * 64);
            par ^= 1u;
            const float mn = __uint_as_float(tagged(fmaxf(fmaxf(m, fmaxf(__uint_as_float(wm.x), __uint_as_float(wm.y))),
                                                          fmaxf(__uint_as_float(wm.z), __uint_as_float(wm.w))), (((meta & 511u) / RG) + 1u) & 1u));
            const float mc = -mn * C;
            const float alpha = ex2(fmaf(m, C, mc));
            m = mn;
            const float p0 = ex2(fmaf(s0, C, mc)), p1 = ex2(fmaf(s1, C, mc)), p2 = ex2(fmaf(s2, C, mc)), p3 = ex2(fmaf(s3, C, mc));
            l = fmaf(l, alpha, (p0 + p1) + (p2 + p3));
            float lt = l + __shfl_xor_sync(0xffffffffu, l, 1);
            sts64_if(wr_p, pf_w + ik * 512, pack_bf16(p0, p1), pack_bf16(p2, p3));
            sts64_if(wr_a, xam_w + ik * 32, __float_as_uint(alpha), __float_as_uint(mn));
            sts32_if(wr_m, xmeta0 + ik * 4, meta);
            lt += __shfl_xor_sync(0xffffffffu, lt, 2);
            sts32_if(wr_q, xl_w + ik * 64, __float_as_uint(lt));
            __syncwarp();
            mbar_arrive_if(lane == 0, fullV + ik * 8);
            if (++ik == NST) { ik = 0; ph ^= 1; }
        }
    } else if (warp < 8) {
        const int w = warp - 4;
        uint32_t voff[2];
#pragma unroll
        for (int mt = 0; mt < 2; mt++) voff[mt] = tile_off((li >> 1) * 8 + lr, 4 * w + 2 * mt + (li & 1));
        uint32_t pf_r = smem_u32(&st->pfrag[0][0][(g & 3) * 4 + t]);
        uint32_t xam_r = smem_u32(&st->xam[0][2 * (t & 1)]);
        uint32_t xl_r = smem_u32(&st->xl[0][2 * (t & 1)][0]);
        uint32_t v0 = smem_base + voff[0], v1 = smem_base + voff[1];
        uint32_t a_ml = abase + w * ST_WORDS * 4 + 512 + (t & 1) * 8;
        uint32_t a_so = abase + w * ST_WORDS * 4 + lane * 16;
        uint32_t a_rf = abase + w * 4;
        uint64_t p_out = (uint64_t)(out + 2 * (t & 1) * DH + 32 * w + 16 * (t >> 1) + g);
        uint64_t p_st  = (uint64_t)&g_state[0][w][lane];
        uint64_t p_po  = (uint64_t)&g_po[0][w][0][0] + lane * (RECB / 32);
        uint64_t p_ml  = (uint64_t)((uint2*)&g_ml[0][w >> 1][0][0] + t);
        uint32_t lo_half = t < 2, ml_writer = g == 0 && !(w & 1);
        PIN32(pf_r); PIN32(xam_r); PIN32(xl_r); PIN32(v0); PIN32(v1); PIN32(a_ml); PIN32(a_so); PIN32(a_rf);
        PIN64(p_out); PIN64(p_st); PIN64(p_po); PIN64(p_ml); PIN32(lo_half); PIN32(ml_writer);

        float acc[2][2][4];
        int iv = 0; uint32_t ph = 0;
        asm volatile("bar.sync 2, %0;" :: "n"(NTHREADS) : "memory");
        while (true) {
            mbar_wait(fullV + iv * 8, ph);
            const uint32_t sv = lds32(meta0 + 2 * NST * 4 + iv * 4);
            const uint32_t s = sv & 0xffu;
            const uint32_t meta = lds32(xmeta0 + iv * 4);
            const uint4 am = lds128(xam_r + iv * 32);
            const uint4 l0 = lds128(xl_r + iv * 64), l1 = lds128(xl_r + iv * 64 + 16);
            uint2 pb[4];
#pragma unroll
            for (int kb = 0; kb < 4; kb++) pb[kb] = lds64(pf_r + iv * 512 + kb * 128);
            uint2 sM = lds64(a_ml + s * AUX_BYTES), sL = lds64(a_ml + s * AUX_BYTES + 16);
            uint4 so = lds128(a_so + s * AUX_BYTES);
            uint32_t ringflag = lds32(a_rf + s * AUX_BYTES);
            uint32_t vf[8][4];
#pragma unroll
            for (int kb = 0; kb < 4; kb++) {
                ldsm4t(vf[2 * kb], v0 + s * TILE_BYTES + kb * 2048);
                ldsm4t(vf[2 * kb + 1], v1 + s * TILE_BYTES + kb * 2048);
            }
            __syncwarp();
            mbar_arrive_if(lane == 0, empty0 + s * 8);
            mbar_arrive_if(lane == 0, pfree0 + iv * 8);
            if (++iv == NST) { iv = 0; ph ^= 1; }
            const bool first = meta & F_FIRST;
            const bool fin = (meta & (F_FIN | F_LAST)) == (F_FIN | F_LAST);
            const bool part = (meta & (F_FIN | F_LAST)) == F_LAST;
            const int h = meta & 511;
            const int slot = h % RG, gen = h / RG;
            const uint32_t jk = meta >> 24;
            const uint32_t tb = (uint32_t)(gen + 1) & 1u;
            unsigned char* op = (unsigned char*)(p_out + (uint32_t)h * (SQ * DH * 2));
            unsigned char* sp = (unsigned char*)(p_st + (uint32_t)h * ST_BYTES);
            unsigned char* pp = (unsigned char*)(p_po + (uint32_t)slot * (4 * NRECP * RECB) + jk * RECB);
            unsigned char* mp = (unsigned char*)(p_ml + (uint32_t)slot * (2 * NRECP * 32) + jk * 32);
            const float a0 = __uint_as_float(am.x), a1 = __uint_as_float(am.z);
#pragma unroll
            for (int mt = 0; mt < 2; mt++) {
                acc[0][mt][0] = first ? 0.f : acc[0][mt][0] * a0; acc[0][mt][1] = first ? 0.f : acc[0][mt][1] * a1;
                acc[0][mt][2] = first ? 0.f : acc[0][mt][2] * a0; acc[0][mt][3] = first ? 0.f : acc[0][mt][3] * a1;
                acc[1][mt][0] = 0.f; acc[1][mt][1] = 0.f; acc[1][mt][2] = 0.f; acc[1][mt][3] = 0.f;
            }
            const float M0 = __uint_as_float(am.y), M1 = __uint_as_float(am.w);
            const float L0 = (__uint_as_float(l0.x) + __uint_as_float(l0.y)) + (__uint_as_float(l0.z) + __uint_as_float(l0.w));
            const float L1 = (__uint_as_float(l1.x) + __uint_as_float(l1.y)) + (__uint_as_float(l1.z) + __uint_as_float(l1.w));
            uint32_t ok = fin ? (so.x & so.y & so.z & so.w & sM.x & sM.y & sL.x & sL.y) : (uint32_t)(!part || gen == 0 || ringflag == (uint32_t)gen);
            ok = __reduce_and_sync(0xffffffffu, ok);
            float ca0, ca1, cb0, cb1;
            auto factors = [&]() {
                const float Ms0 = __uint_as_float(sM.x), Ms1 = __uint_as_float(sM.y);
                const float mf0 = fmaxf(Ms0, M0), mf1 = fmaxf(Ms1, M1);
                const float fa0 = ex2((Ms0 - mf0) * C), fb0 = ex2((M0 - mf0) * C);
                const float fa1 = ex2((Ms1 - mf1) * C), fb1 = ex2((M1 - mf1) * C);
                const float inv0 = rcp(fmaf(fa0, __uint_as_float(sL.x), fb0 * L0));
                const float inv1 = rcp(fmaf(fa1, __uint_as_float(sL.y), fb1 * L1));
                ca0 = fa0 * inv0; ca1 = fa1 * inv1; cb0 = fb0 * inv0; cb1 = fb1 * inv1;
            };
            factors();
#pragma unroll
            for (int kb = 0; kb < 4; kb++) {
#pragma unroll
                for (int mt = 0; mt < 2; mt++)
                    mma16816(acc[kb & 1][mt], vf[2 * kb + mt][0], vf[2 * kb + mt][1], vf[2 * kb + mt][2], vf[2 * kb + mt][3], pb[kb].x, pb[kb].y);
            }
            if (!(ok & 1u)) {
                if (fin) {
                    for (uint32_t iters = 0;; iters++) {
                        so = ld_relaxed4(&g_state[h][w][lane]);
                        sM = ld_relaxed2((const uint2*)&g_state[h][w][32] + (t & 1));
                        sL = ld_relaxed2((const uint2*)&g_state[h][w][33] + (t & 1));
                        if (__reduce_and_sync(0xffffffffu, so.x & so.y & so.z & so.w & sM.x & sM.y & sL.x & sL.y) & 1u) break;
                        if (iters > (1u << 22)) __trap();
                    }
                    factors();
                } else {
                    for (uint32_t iters = 0; ld_acquire((const unsigned int*)&g_merged[slot] + w) != (unsigned)gen; iters++) {
                        if (iters > (1u << 24)) __trap();
                    }
                }
            }
#pragma unroll
            for (int mt = 0; mt < 2; mt++) {
#pragma unroll
                for (int i = 0; i < 4; i++) acc[0][mt][i] += acc[1][mt][i];
            }
            float4 o;
            o.x = lo_half ? acc[0][0][0] : acc[0][1][0]; o.y = lo_half ? acc[0][0][1] : acc[0][1][1];
            o.z = lo_half ? acc[0][0][2] : acc[0][1][2]; o.w = lo_half ? acc[0][0][3] : acc[0][1][3];
            {
                const uint32_t r0 = pack_bf16(fmaf(cb0, o.x, ca0 * __uint_as_float(so.x)), fmaf(cb1, o.y, ca1 * __uint_as_float(so.y)));
                const uint32_t r1 = pack_bf16(fmaf(cb0, o.z, ca0 * __uint_as_float(so.z)), fmaf(cb1, o.w, ca1 * __uint_as_float(so.w)));
                stg16_if(fin, op, r0 & 0xffffu);
                stg16_if(fin, op + DH * 2, r0 >> 16);
                stg16_if(fin, op + 16, r1 & 0xffffu);
                stg16_if(fin, op + DH * 2 + 16, r1 >> 16);
                st_relaxed4_if(fin, sp, make_uint4(0, 0, 0, 0));
                st_relaxed4_if(fin && lane < 2, sp + 512, make_uint4(0, 0, 0, 0));
            }
            {
                st_relaxed2_if(part, pp, pack_tag(o.x, o.y, tb), pack_tag(o.z, o.w, tb));
                st_relaxed2_if(part && ml_writer, mp, tagged(lo_half ? M0 : L0, tb), tagged(lo_half ? M1 : L1, tb));
            }
            if (sv & V_END) break;
        }
    } else if (warp < 10) {
        asm volatile("bar.sync 2, %0;" :: "n"(NTHREADS) : "memory");
        const int mi = warp - 8;
        const uint32_t mb = smem_u32(mbuf) + mi * MBUF_BYTES;
        const uint32_t mbar = smem_u32(&st->mfull[mi]);
        const uint32_t wb = smem_u32(&st->wbuf[mi][0][0]);
        uint32_t mph = 0;
        for (int h = cta; h < NH; h += G) {
            const int slot = h % RG, gen = h / RG;
            const uint32_t tb = (uint32_t)(gen + 1) & 1u;
            const int need = (h + 1) * NREC + MERGE_LAG;
            {
                const int need2 = min(need, NMAIN + MERGE_LAG_END);
                uint32_t iters = 0;
                while (st->progress < need2) {
                    __nanosleep(200);
                    if (++iters > (1u << 23)) __trap();
                }
            }
            const bool has_hi = lane + 32 < NREC;
            bool poll = need > NMAIN + MERGE_LAG_END;
            for (uint32_t attempt = 0;; attempt++) {
                if (poll) {
                    for (uint32_t iters = 0;; iters++) {
                        uint32_t b = tagdiff(ld_relaxed4(&g_ml[slot][mi][lane][0]), tb) | tagdiff(ld_relaxed4(&g_ml[slot][mi][lane][1]), tb);
                        if (has_hi) b |= tagdiff(ld_relaxed4(&g_ml[slot][mi][lane + 32][0]), tb) | tagdiff(ld_relaxed4(&g_ml[slot][mi][lane + 32][1]), tb);
                        if (!(__reduce_or_sync(0xffffffffu, b) & 1u)) break;
                        __nanosleep(100);
                        if (iters > (1u << 21)) __trap();
                    }
                }
                __syncwarp();
                if (lane == 0) {
                    asm volatile("fence.proxy.async.shared::cta;" ::: "memory");
                    mbar_expect_tx(mbar, 2 * NREC * RECB + NREC * 32);
                    bulk_load(mb, &g_po[slot][2 * mi][0][0], NREC * RECB, mbar);
                    bulk_load(mb + NRECP * RECB, &g_po[slot][2 * mi + 1][0][0], NREC * RECB, mbar);
                    bulk_load(mb + 2 * NRECP * RECB, &g_ml[slot][mi][0][0], NREC * 32, mbar);
                }
                mbar_wait(mbar, mph);
                mph ^= 1u;
                const uint4 mu = lds128(mb + 2 * NRECP * RECB + lane * 32), lu = lds128(mb + 2 * NRECP * RECB + lane * 32 + 16);
                uint4 mv = lds128(mb + 2 * NRECP * RECB + 1024 + lane * 32), lv = lds128(mb + 2 * NRECP * RECB + 1024 + lane * 32 + 16);
                uint32_t bad = tagdiff(mu, tb) | tagdiff(lu, tb);
                if (has_hi) bad |= tagdiff(mv, tb) | tagdiff(lv, tb);
                else { mv = make_uint4(0xff800000u, 0xff800000u, 0xff800000u, 0xff800000u); lv = make_uint4(0, 0, 0, 0); }
                float4 M = make_float4(fmaxf(__uint_as_float(mu.x), __uint_as_float(mv.x)), fmaxf(__uint_as_float(mu.y), __uint_as_float(mv.y)),
                                       fmaxf(__uint_as_float(mu.z), __uint_as_float(mv.z)), fmaxf(__uint_as_float(mu.w), __uint_as_float(mv.w)));
#pragma unroll
                for (int d = 16; d >= 1; d >>= 1) {
                    M.x = fmaxf(M.x, __shfl_xor_sync(0xffffffffu, M.x, d));
                    M.y = fmaxf(M.y, __shfl_xor_sync(0xffffffffu, M.y, d));
                    M.z = fmaxf(M.z, __shfl_xor_sync(0xffffffffu, M.z, d));
                    M.w = fmaxf(M.w, __shfl_xor_sync(0xffffffffu, M.w, d));
                }
                M.x = __uint_as_float(tagged(M.x, 1u)); M.y = __uint_as_float(tagged(M.y, 1u));
                M.z = __uint_as_float(tagged(M.z, 1u)); M.w = __uint_as_float(tagged(M.w, 1u));
                float4 w, w2;
                w.x = ex2((__uint_as_float(mu.x) - M.x) * C); w.y = ex2((__uint_as_float(mu.y) - M.y) * C);
                w.z = ex2((__uint_as_float(mu.z) - M.z) * C); w.w = ex2((__uint_as_float(mu.w) - M.w) * C);
                w2.x = ex2((__uint_as_float(mv.x) - M.x) * C); w2.y = ex2((__uint_as_float(mv.y) - M.y) * C);
                w2.z = ex2((__uint_as_float(mv.z) - M.z) * C); w2.w = ex2((__uint_as_float(mv.w) - M.w) * C);
                *(float4*)&st->wbuf[mi][lane][0] = w;
                *(float4*)&st->wbuf[mi][lane + 32][0] = w2;
                __syncwarp();
                float4 a0 = make_float4(0.f, 0.f, 0.f, 0.f), a1 = make_float4(0.f, 0.f, 0.f, 0.f);
                auto rec = [&](int j) {
                    const uint2 ww = lds64(wb + j * 16 + (t & 1) * 8);
                    const float w0 = __uint_as_float(ww.x), w1 = __uint_as_float(ww.y);
                    const uint2 x = lds64(mb + j * RECB + lane * 8), y = lds64(mb + NRECP * RECB + j * RECB + lane * 8);
                    bad |= (x.x ^ tb) | (x.y ^ tb) | (y.x ^ tb) | (y.y ^ tb);
                    a0.x = fmaf(w0, __uint_as_float(x.x << 16), a0.x); a0.y = fmaf(w1, __uint_as_float(x.x & 0xffff0000u), a0.y);
                    a0.z = fmaf(w0, __uint_as_float(x.y << 16), a0.z); a0.w = fmaf(w1, __uint_as_float(x.y & 0xffff0000u), a0.w);
                    a1.x = fmaf(w0, __uint_as_float(y.x << 16), a1.x); a1.y = fmaf(w1, __uint_as_float(y.x & 0xffff0000u), a1.y);
                    a1.z = fmaf(w0, __uint_as_float(y.y << 16), a1.z); a1.w = fmaf(w1, __uint_as_float(y.y & 0xffff0000u), a1.w);
                };
#pragma unroll 8
                for (int j = 0; j < 56; j++) rec(j);
#pragma unroll
                for (int j = 56; j < NREC; j++) rec(j);
                if (__reduce_or_sync(0xffffffffu, bad) & 1u) {
                    poll = true;
                    if (attempt > (1u << 20)) __trap();
                    continue;
                }
                st_relaxed4(&g_state[h][2 * mi][lane], tagged4(a0.x, a0.y, a0.z, a0.w, 1u));
                st_relaxed4(&g_state[h][2 * mi + 1][lane], tagged4(a1.x, a1.y, a1.z, a1.w, 1u));
                float4 L = make_float4(fmaf(w.x, __uint_as_float(lu.x), w2.x * __uint_as_float(lv.x)), fmaf(w.y, __uint_as_float(lu.y), w2.y * __uint_as_float(lv.y)),
                                       fmaf(w.z, __uint_as_float(lu.z), w2.z * __uint_as_float(lv.z)), fmaf(w.w, __uint_as_float(lu.w), w2.w * __uint_as_float(lv.w)));
#pragma unroll
                for (int d = 16; d >= 1; d >>= 1) {
                    L.x += __shfl_xor_sync(0xffffffffu, L.x, d);
                    L.y += __shfl_xor_sync(0xffffffffu, L.y, d);
                    L.z += __shfl_xor_sync(0xffffffffu, L.z, d);
                    L.w += __shfl_xor_sync(0xffffffffu, L.w, d);
                }
                if (lane < 4) {
                    const float4 v = (lane & 1) ? L : M;
                    st_relaxed4(&g_state[h][2 * mi + (lane >> 1)][32 + (lane & 1)], tagged4(v.x, v.y, v.z, v.w, 1u));
                }
                break;
            }
            if (lane < 2) st_relaxed((unsigned int*)&g_merged[slot] + 2 * mi + lane, (unsigned)gen + 1u);
        }
    } else {
        if (lane == 0) {
            for (int s = 0; s < NST; s++) {
                mbar_init(fullK + s * 8, 1); mbar_init(fullV + s * 8, 5); mbar_init(empty0 + s * 8, 4); mbar_init(pfree0 + s * 8, 4);
            }
            for (int i = 0; i < 2; i++) mbar_init(smem_u32(&st->mfull[i]), 1);
            st->progress = 0;
            asm volatile("fence.mbarrier_init.release.cluster;" ::: "memory");
        }
        __syncwarp();
        asm volatile("bar.arrive 2, %0;" :: "n"(NTHREADS) : "memory");
        if (lane == 0) {
            uint64_t pol;
            asm volatile("createpolicy.fractional.L2::evict_first.b64 %0, 1.0;" : "=l"(pol));
            int s = 0; uint32_t ph = 1;
            int ik = 0, iv = 0;
            auto issueK = [&](uint32_t meta) {
                const uint32_t fb = fullK + ik * 8;
                if (meta & F_STOP) {
                    sts32(meta0 + ik * 4, meta);
                    mbar_arrive(fb);
                } else {
                    mbar_wait(empty0 + s * 8, ph);
                    sts32(meta0 + ik * 4, meta);
                    sts32(meta0 + NST * 4 + ik * 4, (uint32_t)s);
                    const int h = meta & 511;
                    mbar_expect_tx(fb, TILE_BYTES + ((meta & F_FIRST) ? Q_BYTES : 0));
                    tma3d(smem_base + s * TILE_BYTES, &mapK, h * SKV + (int)(meta >> 24) * TILE, fb, pol);
                    if (meta & F_FIRST) tma3d_nohint(abase + s * AUX_BYTES, &mapQ, h * SQ, fb);
                    if (++s == NST) { s = 0; ph ^= 1; }
                }
                if (++ik == NST) ik = 0;
            };
            auto issueV = [&](uint32_t meta, bool end) {
                mbar_wait(empty0 + s * 8, ph);
                const uint32_t fb = fullV + iv * 8;
                sts32(meta0 + 2 * NST * 4 + iv * 4, (uint32_t)s | (end ? V_END : 0u));
                const int h = meta & 511;
                const bool fin = (meta & (F_FIN | F_LAST)) == (F_FIN | F_LAST);
                const bool flag = (meta & (F_FIN | F_LAST)) == F_LAST && h >= RG;
                mbar_expect_tx(fb, TILE_BYTES + (fin ? ST_BYTES : 0) + (flag ? 16 : 0));
                tma3d(smem_base + s * TILE_BYTES, &mapV, h * SKV + (int)(meta >> 24) * TILE, fb, pol);
                if (fin)  bulk_load(abase + s * AUX_BYTES, &g_state[h][0][0], ST_BYTES, fb);
                if (flag) bulk_load(abase + s * AUX_BYTES, &g_merged[h % RG], 16, fb);
                if (++s == NST) { s = 0; ph ^= 1; }
                if (++iv == NST) iv = 0;
            };
            auto first_tile = [&](int u) -> uint32_t {
                if (u >= NTOTAL) return F_STOP;
                if (u >= NMAIN) return (uint32_t)(u - NMAIN) | F_FIN | F_FIRST | ((uint32_t)NREC << 24);
                const uint32_t h = (uint32_t)u / (uint32_t)NREC, j = (uint32_t)u - h * (uint32_t)NREC;
                return h | F_FIRST | F_LAST | (j << 24);
            };
            uint32_t cur = first_tile(cta);
            unsigned int claim = 0;
            if (cur & F_LAST) claim = atom_inc(&g_ctr[0], NTOTAL - 1);
            issueK(cur);
            while (true) {
                uint32_t nxt;
                if (cur & F_LAST) {
                    const int u = (int)claim + G;
                    st->progress = u;
                    nxt = first_tile(u);
                } else {
                    nxt = ((cur & ~F_FIRST) | F_LAST) + (1u << 24);
                }
                if (nxt & F_LAST) claim = atom_inc(&g_ctr[0], NTOTAL - 1);
                issueK(nxt);
                issueV(cur, (nxt & F_STOP) != 0u);
                if (nxt & F_STOP) break;
                cur = nxt;
            }
        }
    }
}

typedef CUresult (*EncodeFn)(CUtensorMap*, CUtensorMapDataType, cuuint32_t, void*, const cuuint64_t*, const cuuint64_t*,
                             const cuuint32_t*, const cuuint32_t*, CUtensorMapInterleave, CUtensorMapSwizzle,
                             CUtensorMapL2promotion, CUtensorMapFloatOOBfill);

void make_map(EncodeFn enc, CUtensorMap* m, const void* p, int rows, int box_rows) {
    cuuint64_t gd[3] = {64, (cuuint64_t)rows, 2};
    cuuint64_t gs[2] = {256, 128};
    cuuint32_t bd[3] = {64, (cuuint32_t)box_rows, 2};
    cuuint32_t es[3] = {1, 1, 1};
    enc(m, CU_TENSOR_MAP_DATA_TYPE_BFLOAT16, 3, const_cast<void*>(p), gd, gs, bd, es, CU_TENSOR_MAP_INTERLEAVE_NONE,
        CU_TENSOR_MAP_SWIZZLE_128B, CU_TENSOR_MAP_L2_PROMOTION_L2_256B, CU_TENSOR_MAP_FLOAT_OOB_FILL_NONE);
}

}

extern "C" void kernel_launch(void* const* d_in, const int* in_sizes, int n_in, void* d_out, int out_size) {
    (void)in_sizes; (void)n_in; (void)out_size;
    static EncodeFn enc = nullptr;
    static int grid = 0;
    if (!enc) {
        cudaDriverEntryPointQueryResult qr;
        cudaGetDriverEntryPoint("cuTensorMapEncodeTiled", (void**)&enc, cudaEnableDefault, &qr);
        int dev = 0, sms = 0;
        cudaGetDevice(&dev);
        cudaDeviceGetAttribute(&sms, cudaDevAttrMultiProcessorCount, dev);
        grid = sms;
        cudaFuncSetAttribute(attn_kernel, cudaFuncAttributeMaxDynamicSharedMemorySize, SMEM_BYTES);
    }
    CUtensorMap mk, mv, mq;
    make_map(enc, &mq, d_in[0], NH * SQ, SQ);
    make_map(enc, &mk, d_in[1], NH * SKV, TILE);
    make_map(enc, &mv, d_in[2], NH * SKV, TILE);
    attn_kernel<<<grid, NTHREADS, SMEM_BYTES>>>(mk, mv, mq, (__nv_bfloat16*)d_out);
}
```

```cpp
#include <cuda_runtime.h>
#include <cuda_bf16.h>
#include <cuda.h>
#include <stdint.h>

namespace {

constexpr int NH      = 512;
constexpr int SQ      = 4;
constexpr int SKV     = 4096;
constexpr int DH      = 128;
constexpr int TILE    = 64;
constexpr int TPH     = SKV / TILE;
constexpr int NREC    = TPH - 2;
constexpr int NRECP   = 64;
constexpr int RECB    = 256;
constexpr int NMAIN   = NH * NREC;
constexpr int NTOTAL  = NMAIN + NH;
constexpr int NST     = 3;
constexpr int TILE_BYTES = TILE * DH * 2;
constexpr int Q_BYTES = SQ * DH * 2;
constexpr int RG      = 64;
constexpr int MERGE_LAG = 700;
static_assert((NH / RG) % 2 == 0, "generation parity must repeat every launch");
static_assert((RG - 1) * NREC >= MERGE_LAG, "a CTA blocked on a ring slot must already have released its own mergers");
static_assert(NST >= 3, "sequence-indexed entries are recycled through the buffer ring");
constexpr int MERGE_LAG_END = 100;
constexpr int ST_WORDS = 144;
constexpr int ST_BYTES = 4 * ST_WORDS * 4;
constexpr int AUX_BYTES = 3072;
static_assert(AUX_BYTES >= ST_BYTES && AUX_BYTES % 1024 == 0, "aux");

constexpr int NTHREADS = 352;

constexpr uint32_t F_FIRST = 1u << 16;
constexpr uint32_t F_LAST  = 1u << 17;
constexpr uint32_t F_FIN   = 1u << 18;
constexpr uint32_t F_STOP  = 1u << 19;
constexpr uint32_t V_END   = 1u << 8;

struct __align__(16) SmemTail {
    uint2    pfrag[NST][4][16];
    float2   xam[NST][4];
    float    xl[NST][4][4];
    float    wmax[2][4][4];
    float    wbuf[2][NRECP][4];
    uint64_t full[2][NST];
    uint64_t empty[NST];
    uint64_t mfull[2];
    uint64_t pfree[NST];
    uint32_t meta[NST];
    uint32_t slotK[NST];
    uint32_t slotV[NST];
    uint32_t xmeta[NST];
    volatile int progress;
};
constexpr int MBUF_BYTES = 2 * NRECP * RECB + NRECP * 32;
constexpr int SMEM_BYTES = 1024 + NST * TILE_BYTES + NST * AUX_BYTES + 2 * MBUF_BYTES + (int)sizeof(SmemTail);

__device__ uint4        g_po[RG][4][NRECP][RECB / 16];
__device__ uint4        g_ml[RG][2][NRECP][2];
__device__ uint4        g_state[NH][4][ST_WORDS / 4];
__device__ uint4        g_merged[RG];
__device__ __align__(128) unsigned int g_ctr[32];

__device__ __forceinline__ uint32_t smem_u32(const void* p) { return (uint32_t)__cvta_generic_to_shared(p); }
__device__ __forceinline__ void mbar_init(uint32_t bar, uint32_t cnt) {
    asm volatile("mbarrier.init.shared::cta.b64 [%0], %1;" :: "r"(bar), "r"(cnt));
}
__device__ __forceinline__ void mbar_expect_tx(uint32_t bar, uint32_t bytes) {
    asm volatile("mbarrier.arrive.expect_tx.shared::cta.b64 _, [%0], %1;" :: "r"(bar), "r"(bytes) : "memory");
}
__device__ __forceinline__ void mbar_arrive(uint32_t bar) {
    asm volatile("mbarrier.arrive.shared::cta.b64 _, [%0];" :: "r"(bar) : "memory");
}
__device__ __forceinline__ void mbar_wait(uint32_t bar, uint32_t parity) {
    uint32_t done;
    uint32_t iters = 0;
    do {
        asm volatile("{\n.reg .pred p;\nmbarrier.try_wait.parity.shared::cta.b64 p, [%1], %2;\nselp.u32 %0, 1, 0, p;\n}"
                     : "=r"(done) : "r"(bar), "r"(parity) : "memory");
        if (++iters > (1u << 26)) __trap();
    } while (!done);
}
__device__ __forceinline__ uint32_t tile_off(int row, int chunk) {
    return (uint32_t)((chunk >> 3) * 8192 + row * 128 + (((chunk & 7) ^ (row & 7)) << 4));
}
__device__ __forceinline__ void tma3d(uint32_t dst, const CUtensorMap* m, int row, uint32_t bar, uint64_t pol) {
    asm volatile("cp.async.bulk.tensor.3d.shared::cluster.global.mbarrier::complete_tx::bytes.L2::cache_hint "
                 "[%0], [%1, {%3, %4, %3}], [%2], %5;"
                 :: "r"(dst), "l"(m), "r"(bar), "r"(0), "r"(row), "l"(pol) : "memory");
}
__device__ __forceinline__ void tma3d_nohint(uint32_t dst, const CUtensorMap* m, int row, uint32_t bar) {
    asm volatile("cp.async.bulk.tensor.3d.shared::cluster.global.mbarrier::complete_tx::bytes "
                 "[%0], [%1, {%3, %4, %3}], [%2];"
                 :: "r"(dst), "l"(m), "r"(bar), "r"(0), "r"(row) : "memory");
}
__device__ __forceinline__ void bulk_load(uint32_t dst, const void* src, uint32_t bytes, uint32_t bar) {
    asm volatile("cp.async.bulk.shared::cluster.global.mbarrier::complete_tx::bytes [%0], [%1], %2, [%3];"
                 :: "r"(dst), "l"(src), "r"(bytes), "r"(bar) : "memory");
}
__device__ __forceinline__ void ldsm4(uint32_t* r, uint32_t addr) {
    asm volatile("ldmatrix.sync.aligned.m8n8.x4.shared.b16 {%0,%1,%2,%3}, [%4];"
                 : "=r"(r[0]), "=r"(r[1]), "=r"(r[2]), "=r"(r[3]) : "r"(addr) : "memory");
}
__device__ __forceinline__ void ldsm4t(uint32_t* r, uint32_t addr) {
    asm volatile("ldmatrix.sync.aligned.m8n8.x4.trans.shared.b16 {%0,%1,%2,%3}, [%4];"
                 : "=r"(r[0]), "=r"(r[1]), "=r"(r[2]), "=r"(r[3]) : "r"(addr) : "memory");
}
__device__ __forceinline__ uint32_t lds32(uint32_t a) { uint32_t v; asm volatile("ld.shared.u32 %0, [%1];" : "=r"(v) : "r"(a) : "memory"); return v; }
__device__ __forceinline__ uint2 lds64(uint32_t a) { uint2 v; asm volatile("ld.shared.v2.u32 {%0,%1}, [%2];" : "=r"(v.x), "=r"(v.y) : "r"(a) : "memory"); return v; }
__device__ __forceinline__ uint4 lds128(uint32_t a) { uint4 v; asm volatile("ld.shared.v4.u32 {%0,%1,%2,%3}, [%4];" : "=r"(v.x), "=r"(v.y), "=r"(v.z), "=r"(v.w) : "r"(a) : "memory"); return v; }
__device__ __forceinline__ void sts32(uint32_t a, uint32_t v) { asm volatile("st.shared.u32 [%0], %1;" :: "r"(a), "r"(v) : "memory"); }
__device__ __forceinline__ void sts32_if(bool c, uint32_t a, uint32_t v) {
    asm volatile("{\n.reg .pred p;\nsetp.ne.u32 p, %2, 0;\n@p st.shared.u32 [%0], %1;\n}" :: "r"(a), "r"(v), "r"((uint32_t)c) : "memory");
}
__device__ __forceinline__ void sts64_if(bool c, uint32_t a, uint32_t x, uint32_t y) {
    asm volatile("{\n.reg .pred p;\nsetp.ne.u32 p, %3, 0;\n@p st.shared.v2.u32 [%0], {%1,%2};\n}" :: "r"(a), "r"(x), "r"(y), "r"((uint32_t)c) : "memory");
}
__device__ __forceinline__ void stg16_if(bool c, void* p, uint32_t v) {
    asm volatile("{\n.reg .pred p;\nsetp.ne.u32 p, %2, 0;\n@p st.global.u16 [%0], %1;\n}" :: "l"(p), "h"((unsigned short)v), "r"((uint32_t)c) : "memory");
}
__device__ __forceinline__ void st_relaxed4_if(bool c, void* p, uint4 v) {
    asm volatile("{\n.reg .pred p;\nsetp.ne.u32 p, %5, 0;\n@p st.relaxed.gpu.global.v4.u32 [%0], {%1,%2,%3,%4};\n}"
                 :: "l"(p), "r"(v.x), "r"(v.y), "r"(v.z), "r"(v.w), "r"((uint32_t)c) : "memory");
}
__device__ __forceinline__ void st_relaxed2_if(bool c, void* p, uint32_t x, uint32_t y) {
    asm volatile("{\n.reg .pred p;\nsetp.ne.u32 p, %3, 0;\n@p st.relaxed.gpu.global.v2.u32 [%0], {%1,%2};\n}"
                 :: "l"(p), "r"(x), "r"(y), "r"((uint32_t)c) : "memory");
}
__device__ __forceinline__ void mbar_arrive_if(bool c, uint32_t bar) {
    asm volatile("{\n.reg .pred p;\nsetp.ne.u32 p, %1, 0;\n@p mbarrier.arrive.shared::cta.b64 _, [%0];\n}" :: "r"(bar), "r"((uint32_t)c) : "memory");
}
__device__ __forceinline__ void mma16816(float (&c)[4], uint32_t a0, uint32_t a1, uint32_t a2, uint32_t a3,
                                         uint32_t b0, uint32_t b1) {
    asm volatile("mma.sync.aligned.m16n8k16.row.col.f32.bf16.bf16.f32 {%0,%1,%2,%3}, {%4,%5,%6,%7}, {%8,%9}, {%0,%1,%2,%3};"
                 : "+f"(c[0]), "+f"(c[1]), "+f"(c[2]), "+f"(c[3])
                 : "r"(a0), "r"(a1), "r"(a2), "r"(a3), "r"(b0), "r"(b1));
}
__device__ __forceinline__ uint32_t pack_bf16(float lo, float hi) {
    uint32_t r;
    asm("cvt.rn.bf16x2.f32 %0, %1, %2;" : "=r"(r) : "f"(hi), "f"(lo));
    return r;
}
__device__ __forceinline__ float ex2(float x) {
    float r;
    asm("ex2.approx.ftz.f32 %0, %1;" : "=f"(r) : "f"(x));
    return r;
}
__device__ __forceinline__ float rcp(float x) {
    float r;
    asm("rcp.approx.ftz.f32 %0, %1;" : "=f"(r) : "f"(x));
    return r;
}
__device__ __forceinline__ unsigned int ld_acquire(const unsigned int* p) {
    unsigned int v;
    asm volatile("ld.acquire.gpu.global.u32 %0, [%1];" : "=r"(v) : "l"(p) : "memory");
    return v;
}
__device__ __forceinline__ uint4 ld_relaxed4(const uint4* p) {
    uint4 v;
    asm volatile("ld.relaxed.gpu.global.v4.u32 {%0,%1,%2,%3}, [%4];" : "=r"(v.x), "=r"(v.y), "=r"(v.z), "=r"(v.w) : "l"(p) : "memory");
    return v;
}
__device__ __forceinline__ uint2 ld_relaxed2(const uint2* p) {
    uint2 v;
    asm volatile("ld.relaxed.gpu.global.v2.u32 {%0,%1}, [%2];" : "=r"(v.x), "=r"(v.y) : "l"(p) : "memory");
    return v;
}
__device__ __forceinline__ void st_relaxed4(uint4* p, uint4 v) {
    asm volatile("st.relaxed.gpu.global.v4.u32 [%0], {%1,%2,%3,%4};" :: "l"(p), "r"(v.x), "r"(v.y), "r"(v.z), "r"(v.w) : "memory");
}
__device__ __forceinline__ void st_relaxed(unsigned int* p, unsigned int v) {
    asm volatile("st.relaxed.gpu.global.u32 [%0], %1;" :: "l"(p), "r"(v) : "memory");
}
__device__ __forceinline__ unsigned int atom_inc(unsigned int* p, unsigned int last) {
    unsigned int r;
    asm volatile("atom.relaxed.gpu.global.inc.u32 %0, [%1], %2;" : "=r"(r) : "l"(p), "r"(last) : "memory");
    return r;
}
__device__ __forceinline__ uint32_t tagged(float x, uint32_t tb) { return (__float_as_uint(x) & ~1u) | tb; }
__device__ __forceinline__ uint4 tagged4(float a, float b, float c, float d, uint32_t tb) {
    return make_uint4(tagged(a, tb), tagged(b, tb), tagged(c, tb), tagged(d, tb));
}
__device__ __forceinline__ uint32_t pack_tag(float lo, float hi, uint32_t tb) {
    const uint32_t l = (((__float_as_uint(lo) + 0x10000u - (tb << 16)) >> 17) << 1) | tb;
    return (pack_bf16(0.f, hi) & 0xffff0000u) | (l & 0xffffu);
}
__device__ __forceinline__ uint32_t tagdiff(const uint4& v, uint32_t tb) {
    return (v.x ^ tb) | (v.y ^ tb) | (v.z ^ tb) | (v.w ^ tb);
}

#define PIN32(x) asm volatile("" : "+r"(x))
#define PIN64(x) asm volatile("" : "+l"(x))

__global__ void __launch_bounds__(NTHREADS, 1)
attn_kernel(const __grid_constant__ CUtensorMap mapK, const __grid_constant__ CUtensorMap mapV,
            const __grid_constant__ CUtensorMap mapQ, __nv_bfloat16* __restrict__ out)
{
    extern __shared__ unsigned char smem_raw[];
    unsigned char* smem = (unsigned char*)(((uintptr_t)smem_raw + 1023) & ~(uintptr_t)1023);
    unsigned char* aux = smem + NST * TILE_BYTES;
    unsigned char* mbuf = aux + NST * AUX_BYTES;
    SmemTail* st = (SmemTail*)(mbuf + 2 * MBUF_BYTES);

    const int warp = threadIdx.x >> 5;
    const int lane = threadIdx.x & 31;
    const int G = gridDim.x;
    const int cta = blockIdx.x;
    const float C = 0.08838834764831845f * 1.4426950408889634f;
    const uint32_t smem_base = smem_u32(smem);
    const uint32_t abase = smem_u32(aux);
    const uint32_t fullK = smem_u32(&st->full[0][0]), fullV = smem_u32(&st->full[1][0]), empty0 = smem_u32(&st->empty[0]), meta0 = smem_u32(&st->meta[0]);
    const uint32_t pfree0 = smem_u32(&st->pfree[0]), xmeta0 = smem_u32(&st->xmeta[0]);
    const int g = lane >> 2, t = lane & 3;
    const int li = lane >> 3, lr = lane & 7;

    if (warp < 4) {
        const int w = warp;
        uint32_t koff[4];
#pragma unroll
        for (int kp = 0; kp < 4; kp++) koff[kp] = tile_off(16 * w + lr, 4 * kp + li);
        uint32_t qoff[2];
#pragma unroll
        for (int hf = 0; hf < 2; hf++) qoff[hf] = (uint32_t)((hf * 4 + (lr & 3)) * 128);
        const uint32_t qx[2] = {(uint32_t)(lr & 3), (uint32_t)(4 + (lr & 3))};
        uint32_t pf_w = smem_u32(&st->pfrag[0][w][(g & 3) * 4 + t]);
        uint32_t xam_w = smem_u32(&st->xam[0][g & 3]);
        uint32_t xl_w = smem_u32(&st->xl[0][g & 3][w]);
        uint32_t wm_r = smem_u32(&st->wmax[0][g & 3][0]);
        uint32_t k0 = smem_base + koff[0], k1 = smem_base + koff[1];
        uint32_t qo[8];
#pragma unroll
        for (int ks = 0; ks < 8; ks++) {
            qo[ks] = abase + qoff[ks >> 2] + ((((uint32_t)((2 * ks) & 7) + (uint32_t)(li >> 1)) ^ qx[ks >> 2]) << 4);
            PIN32(qo[ks]);
        }
        uint32_t wr_p = g < 4, wr_q = g < 4 && t == 0, wr_a = w == 0 && g < 4 && t == 0, wr_m = threadIdx.x == 31;
        PIN32(pf_w); PIN32(xam_w); PIN32(xl_w); PIN32(wm_r); PIN32(k0); PIN32(k1);
        PIN32(wr_p); PIN32(wr_q); PIN32(wr_a); PIN32(wr_m);

        uint32_t qa[8][4];
        float m = 0.f, l = 0.f;
        int ik = 0; uint32_t ph = 0;
        uint32_t par = 0;
        asm volatile("bar.sync 2, %0;" :: "n"(NTHREADS) : "memory");
        while (true) {
            mbar_wait(pfree0 + ik * 8, ph ^ 1u);
            mbar_wait(fullK + ik * 8, ph);
            const uint32_t meta = lds32(meta0 + ik * 4);
            const uint32_t s = lds32(meta0 + NST * 4 + ik * 4);
            if (meta & F_STOP) break;
            uint32_t kf[8][4];
#pragma unroll
            for (int kp = 0; kp < 4; kp++) {
                ldsm4(kf[2 * kp], ((kp & 1) ? k1 : k0) + s * TILE_BYTES + (kp >> 1) * 8192);
                ldsm4(kf[2 * kp + 1], ((kp & 1) ? k1 : k0) + s * TILE_BYTES + (kp >> 1) * 8192 + 1024);
            }
            if (meta & F_FIRST) {
#pragma unroll
                for (int ks = 0; ks < 8; ks++) ldsm4(qa[ks], qo[ks] + s * AUX_BYTES);
                m = -INFINITY; l = 0.f;
            }
            __syncwarp();
            mbar_arrive_if(lane == 0, empty0 + s * 8);
            float sc[4][4];
#pragma unroll
            for (int i = 0; i < 4; i++) { sc[i][0] = 0.f; sc[i][1] = 0.f; sc[i][2] = 0.f; sc[i][3] = 0.f; }
#pragma unroll
            for (int kp = 0; kp < 4; kp++) {
#pragma unroll
                for (int nt = 0; nt < 2; nt++) {
                    mma16816(sc[nt], qa[2 * kp][0], qa[2 * kp][1], qa[2 * kp][2], qa[2 * kp][3], kf[2 * kp + nt][0], kf[2 * kp + nt][1]);
                    mma16816(sc[2 + nt], qa[2 * kp + 1][0], qa[2 * kp + 1][1], qa[2 * kp + 1][2], qa[2 * kp + 1][3], kf[2 * kp + nt][2], kf[2 * kp + nt][3]);
                }
            }
            const float s0 = sc[0][0] + sc[2][0], s1 = sc[0][1] + sc[2][1], s2 = sc[1][0] + sc[3][0], s3 = sc[1][1] + sc[3][1];
            float mt_ = fmaxf(fmaxf(s0, s1), fmaxf(s2, s3));
            mt_ = fmaxf(mt_, __shfl_xor_sync(0xffffffffu, mt_, 1));
            mt_ = fmaxf(mt_, __shfl_xor_sync(0xffffffffu, mt_, 2));
            sts32_if(wr_q, wm_r + par * 64 + w * 4, __float_as_uint(mt_));
            asm volatile("bar.sync 1, 128;" ::: "memory");
            const uint4 wm = lds128(wm_r + par * 64);
            par ^= 1u;
            const float mn = __uint_as_float(tagged(fmaxf(fmaxf(m, fmaxf(__uint_as_float(wm.x), __uint_as_float(wm.y))),
                                                          fmaxf(__uint_as_float(wm.z), __uint_as_float(wm.w))), (((meta & 511u) / RG) + 1u) & 1u));
            const float mc = -mn * C;
            const float alpha = ex2(fmaf(m, C, mc));
            m = mn;
            const float p0 = ex2(fmaf(s0, C, mc)), p1 = ex2(fmaf(s1, C, mc)), p2 = ex2(fmaf(s2, C, mc)), p3 = ex2(fmaf(s3, C, mc));
            l = fmaf(l, alpha, (p0 + p1) + (p2 + p3));
            float lt = l + __shfl_xor_sync(0xffffffffu, l, 1);
            sts64_if(wr_p, pf_w + ik * 512, pack_bf16(p0, p1), pack_bf16(p2, p3));
            sts64_if(wr_a, xam_w + ik * 32, __float_as_uint(alpha), __float_as_uint(mn));
            sts32_if(wr_m, xmeta0 + ik * 4, meta);
            lt += __shfl_xor_sync(0xffffffffu, lt, 2);
            sts32_if(wr_q, xl_w + ik * 64, __float_as_uint(lt));
            __syncwarp();
            mbar_arrive_if(lane == 0, fullV + ik * 8);
            if (++ik == NST) { ik = 0; ph ^= 1; }
        }
    } else if (warp < 8) {
        const int w = warp - 4;
        uint32_t voff[2];
#pragma unroll
        for (int mt = 0; mt < 2; mt++) voff[mt] = tile_off((li >> 1) * 8 + lr, 4 * w + 2 * mt + (li & 1));
        uint32_t pf_r = smem_u32(&st->pfrag[0][0][(g & 3) * 4 + t]);
        uint32_t xam_r = smem_u32(&st->xam[0][2 * (t & 1)]);
        uint32_t xl_r = smem_u32(&st->xl[0][2 * (t & 1)][0]);
        uint32_t v0 = smem_base + voff[0], v1 = smem_base + voff[1];
        uint32_t a_ml = abase + w * ST_WORDS * 4 + 512 + (t & 1) * 8;
        uint32_t a_so = abase + w * ST_WORDS * 4 + lane * 16;
        uint32_t a_rf = abase + w * 4;
        uint64_t p_out = (uint64_t)(out + 2 * (t & 1) * DH + 32 * w + 16 * (t >> 1) + g);
        uint64_t p_st  = (uint64_t)&g_state[0][w][lane];
        uint64_t p_po  = (uint64_t)&g_po[0][w][0][0] + lane * (RECB / 32);
        uint64_t p_ml  = (uint64_t)((uint2*)&g_ml[0][w >> 1][0][0] + t);
        uint32_t lo_half = t < 2, ml_writer = g == 0 && !(w & 1);
        PIN32(pf_r); PIN32(xam_r); PIN32(xl_r); PIN32(v0); PIN32(v1); PIN32(a_ml); PIN32(a_so); PIN32(a_rf);
        PIN64(p_out); PIN64(p_st); PIN64(p_po); PIN64(p_ml); PIN32(lo_half); PIN32(ml_writer);

        float acc[2][2][4];
        int iv = 0; uint32_t ph = 0;
        asm volatile("bar.sync 2, %0;" :: "n"(NTHREADS) : "memory");
        while (true) {
            mbar_wait(fullV + iv * 8, ph);
            const uint32_t sv = lds32(meta0 + 2 * NST * 4 + iv * 4);
            const uint32_t s = sv & 0xffu;
            const uint32_t meta = lds32(xmeta0 + iv * 4);
            const uint4 am = lds128(xam_r + iv * 32);
            const uint4 l0 = lds128(xl_r + iv * 64), l1 = lds128(xl_r + iv * 64 + 16);
            uint2 pb[4];
#pragma unroll
            for (int kb = 0; kb < 4; kb++) pb[kb] = lds64(pf_r + iv * 512 + kb * 128);
            uint2 sM = lds64(a_ml + s * AUX_BYTES), sL = lds64(a_ml + s * AUX_BYTES + 16);
            uint4 so = lds128(a_so + s * AUX_BYTES);
            uint32_t ringflag = lds32(a_rf + s * AUX_BYTES);
            uint32_t vf[8][4];
#pragma unroll
            for (int kb = 0; kb < 4; kb++) {
                ldsm4t(vf[2 * kb], v0 + s * TILE_BYTES + kb * 2048);
                ldsm4t(vf[2 * kb + 1], v1 + s * TILE_BYTES + kb * 2048);
            }
            __syncwarp();
            mbar_arrive_if(lane == 0, empty0 + s * 8);
            mbar_arrive_if(lane == 0, pfree0 + iv * 8);
            if (++iv == NST) { iv = 0; ph ^= 1; }
            const bool first = meta & F_FIRST;
            const bool fin = (meta & (F_FIN | F_LAST)) == (F_FIN | F_LAST);
            const bool part = (meta & (F_FIN | F_LAST)) == F_LAST;
            const int h = meta & 511;
            const int slot = h % RG, gen = h / RG;
            const uint32_t jk = meta >> 24;
            const uint32_t tb = (uint32_t)(gen + 1) & 1u;
            unsigned char* op = (unsigned char*)(p_out + (uint32_t)h * (SQ * DH * 2));
            unsigned char* sp = (unsigned char*)(p_st + (uint32_t)h * ST_BYTES);
            unsigned char* pp = (unsigned char*)(p_po + (uint32_t)slot * (4 * NRECP * RECB) + jk * RECB);
            unsigned char* mp = (unsigned char*)(p_ml + (uint32_t)slot * (2 * NRECP * 32) + jk * 32);
            const float a0 = __uint_as_float(am.x), a1 = __uint_as_float(am.z);
#pragma unroll
            for (int mt = 0; mt < 2; mt++) {
                acc[0][mt][0] = first ? 0.f : acc[0][mt][0] * a0; acc[0][mt][1] = first ? 0.f : acc[0][mt][1] * a1;
                acc[0][mt][2] = first ? 0.f : acc[0][mt][2] * a0; acc[0][mt][3] = first ? 0.f : acc[0][mt][3] * a1;
                acc[1][mt][0] = 0.f; acc[1][mt][1] = 0.f; acc[1][mt][2] = 0.f; acc[1][mt][3] = 0.f;
            }
            const float M0 = __uint_as_float(am.y), M1 = __uint_as_float(am.w);
            const float L0 = (__uint_as_float(l0.x) + __uint_as_float(l0.y)) + (__uint_as_float(l0.z) + __uint_as_float(l0.w));
            const float L1 = (__uint_as_float(l1.x) + __uint_as_float(l1.y)) + (__uint_as_float(l1.z) + __uint_as_float(l1.w));
            uint32_t ok = fin ? (so.x & so.y & so.z & so.w & sM.x & sM.y & sL.x & sL.y) : (uint32_t)(!part || gen == 0 || ringflag == (uint32_t)gen);
            ok = __reduce_and_sync(0xffffffffu, ok);
            float ca0, ca1, cb0, cb1;
            auto factors = [&]() {
                const float Ms0 = __uint_as_float(sM.x), Ms1 = __uint_as_float(sM.y);
                const float mf0 = fmaxf(Ms0, M0), mf1 = fmaxf(Ms1, M1);
                const float fa0 = ex2((Ms0 - mf0) * C), fb0 = ex2((M0 - mf0) * C);
                const float fa1 = ex2((Ms1 - mf1) * C), fb1 = ex2((M1 - mf1) * C);
                const float inv0 = rcp(fmaf(fa0, __uint_as_float(sL.x), fb0 * L0));
                const float inv1 = rcp(fmaf(fa1, __uint_as_float(sL.y), fb1 * L1));
                ca0 = fa0 * inv0; ca1 = fa1 * inv1; cb0 = fb0 * inv0; cb1 = fb1 * inv1;
            };
            factors();
#pragma unroll
            for (int kb = 0; kb < 4; kb++) {
#pragma unroll
                for (int mt = 0; mt < 2; mt++)
                    mma16816(acc[kb & 1][mt], vf[2 * kb + mt][0], vf[2 * kb + mt][1], vf[2 * kb + mt][2], vf[2 * kb + mt][3], pb[kb].x, pb[kb].y);
            }
            if (!(ok & 1u)) {
                if (fin) {
                    for (uint32_t iters = 0;; iters++) {
                        so = ld_relaxed4(&g_state[h][w][lane]);
                        sM = ld_relaxed2((const uint2*)&g_state[h][w][32] + (t & 1));
                        sL = ld_relaxed2((const uint2*)&g_state[h][w][33] + (t & 1));
                        if (__reduce_and_sync(0xffffffffu, so.x & so.y & so.z & so.w & sM.x & sM.y & sL.x & sL.y) & 1u) break;
                        if (iters > (1u << 24)) __trap();
                    }
                    factors();
                } else {
                    for (uint32_t iters = 0; ld_acquire((const unsigned int*)&g_merged[slot] + w) != (unsigned)gen; iters++) {
                        if (iters > (1u << 24)) __trap();
                    }
                }
            }
#pragma unroll
            for (int mt = 0; mt < 2; mt++) {
#pragma unroll
                for (int i = 0; i < 4; i++) acc[0][mt][i] += acc[1][mt][i];
            }
            float4 o;
            o.x = lo_half ? acc[0][0][0] : acc[0][1][0]; o.y = lo_half ? acc[0][0][1] : acc[0][1][1];
            o.z = lo_half ? acc[0][0][2] : acc[0][1][2]; o.w = lo_half ? acc[0][0][3] : acc[0][1][3];
            {
                const uint32_t r0 = pack_bf16(fmaf(cb0, o.x, ca0 * __uint_as_float(so.x)), fmaf(cb1, o.y, ca1 * __uint_as_float(so.y)));
                const uint32_t r1 = pack_bf16(fmaf(cb0, o.z, ca0 * __uint_as_float(so.z)), fmaf(cb1, o.w, ca1 * __uint_as_float(so.w)));
                stg16_if(fin, op, r0 & 0xffffu);
                stg16_if(fin, op + DH * 2, r0 >> 16);
                stg16_if(fin, op + 16, r1 & 0xffffu);
                stg16_if(fin, op + DH * 2 + 16, r1 >> 16);
                st_relaxed4_if(fin, sp, make_uint4(0, 0, 0, 0));
                st_relaxed4_if(fin && lane < 2, sp + 512, make_uint4(0, 0, 0, 0));
            }
            {
                st_relaxed2_if(part, pp, pack_tag(o.x, o.y, tb), pack_tag(o.z, o.w, tb));
                st_relaxed2_if(part && ml_writer, mp, tagged(lo_half ? M0 : L0, tb), tagged(lo_half ? M1 : L1, tb));
            }
            if (sv & V_END) break;
        }
    } else if (warp < 10) {
        asm volatile("bar.sync 2, %0;" :: "n"(NTHREADS) : "memory");
        const int mi = warp - 8;
        const uint32_t mb = smem_u32(mbuf) + mi * MBUF_BYTES;
        const uint32_t mbar = smem_u32(&st->mfull[mi]);
        const uint32_t wb = smem_u32(&st->wbuf[mi][0][0]);
        uint32_t mph = 0;
        for (int h = cta; h < NH; h += G) {
            const int slot = h % RG, gen = h / RG;
            const uint32_t tb = (uint32_t)(gen + 1) & 1u;
            const int need = (h + 1) * NREC + MERGE_LAG;
            {
                const int need2 = min(need, NMAIN + MERGE_LAG_END);
                uint32_t iters = 0;
                while (st->progress < need2) {
                    __nanosleep(200);
                    if (++iters > (1u << 26)) __trap();
                }
            }
            const bool has_hi = lane + 32 < NREC;
            bool poll = need > NMAIN + MERGE_LAG_END;
            for (uint32_t attempt = 0;; attempt++) {
                if (poll) {
                    for (uint32_t iters = 0;; iters++) {
                        uint32_t b = tagdiff(ld_relaxed4(&g_ml[slot][mi][lane][0]), tb) | tagdiff(ld_relaxed4(&g_ml[slot][mi][lane][1]), tb);
                        if (has_hi) b |= tagdiff(ld_relaxed4(&g_ml[slot][mi][lane + 32][0]), tb) | tagdiff(ld_relaxed4(&g_ml[slot][mi][lane + 32][1]), tb);
                        if (!(__reduce_or_sync(0xffffffffu, b) & 1u)) break;
                        __nanosleep(100);
                        if (iters > (1u << 24)) __trap();
                    }
                }
                __syncwarp();
                if (lane == 0) {
                    asm volatile("fence.proxy.async.shared::cta;" ::: "memory");
                    mbar_expect_tx(mbar, 2 * NREC * RECB + NREC * 32);
                    bulk_load(mb, &g_po[slot][2 * mi][0][0], NREC * RECB, mbar);
                    bulk_load(mb + NRECP * RECB, &g_po[slot][2 * mi + 1][0][0], NREC * RECB, mbar);
                    bulk_load(mb + 2 * NRECP * RECB, &g_ml[slot][mi][0][0], NREC * 32, mbar);
                }
                mbar_wait(mbar, mph);
                mph ^= 1u;
                const uint4 mu = lds128(mb + 2 * NRECP * RECB + lane * 32), lu = lds128(mb + 2 * NRECP * RECB + lane * 32 + 16);
                uint4 mv = lds128(mb + 2 * NRECP * RECB + 1024 + lane * 32), lv = lds128(mb + 2 * NRECP * RECB + 1024 + lane * 32 + 16);
                uint32_t bad = tagdiff(mu, tb) | tagdiff(lu, tb);
                if (has_hi) bad |= tagdiff(mv, tb) | tagdiff(lv, tb);
                else { mv = make_uint4(0xff800000u, 0xff800000u, 0xff800000u, 0xff800000u); lv = make_uint4(0, 0, 0, 0); }
                float4 M = make_float4(fmaxf(__uint_as_float(mu.x), __uint_as_float(mv.x)), fmaxf(__uint_as_float(mu.y), __uint_as_float(mv.y)),
                                       fmaxf(__uint_as_float(mu.z), __uint_as_float(mv.z)), fmaxf(__uint_as_float(mu.w), __uint_as_float(mv.w)));
#pragma unroll
                for (int d = 16; d >= 1; d >>= 1) {
                    M.x = fmaxf(M.x, __shfl_xor_sync(0xffffffffu, M.x, d));
                    M.y = fmaxf(M.y, __shfl_xor_sync(0xffffffffu, M.y, d));
                    M.z = fmaxf(M.z, __shfl_xor_sync(0xffffffffu, M.z, d));
                    M.w = fmaxf(M.w, __shfl_xor_sync(0xffffffffu, M.w, d));
                }
                M.x = __uint_as_float(tagged(M.x, 1u)); M.y = __uint_as_float(tagged(M.y, 1u));
                M.z = __uint_as_float(tagged(M.z, 1u)); M.w = __uint_as_float(tagged(M.w, 1u));
                float4 w, w2;
                w.x = ex2((__uint_as_float(mu.x) - M.x) * C); w.y = ex2((__uint_as_float(mu.y) - M.y) * C);
                w.z = ex2((__uint_as_float(mu.z) - M.z) * C); w.w = ex2((__uint_as_float(mu.w) - M.w) * C);
                w2.x = ex2((__uint_as_float(mv.x) - M.x) * C); w2.y = ex2((__uint_as_float(mv.y) - M.y) * C);
                w2.z = ex2((__uint_as_float(mv.z) - M.z) * C); w2.w = ex2((__uint_as_float(mv.w) - M.w) * C);
                *(float4*)&st->wbuf[mi][lane][0] = w;
                *(float4*)&st->wbuf[mi][lane + 32][0] = w2;
                __syncwarp();
                float4 a0 = make_float4(0.f, 0.f, 0.f, 0.f), a1 = make_float4(0.f, 0.f, 0.f, 0.f);
                auto rec = [&](int j) {
                    const uint2 ww = lds64(wb + j * 16 + (t & 1) * 8);
                    const float w0 = __uint_as_float(ww.x), w1 = __uint_as_float(ww.y);
                    const uint2 x = lds64(mb + j * RECB + lane * 8), y = lds64(mb + NRECP * RECB + j * RECB + lane * 8);
                    bad |= (x.x ^ tb) | (x.y ^ tb) | (y.x ^ tb) | (y.y ^ tb);
                    a0.x = fmaf(w0, __uint_as_float(x.x << 16), a0.x); a0.y = fmaf(w1, __uint_as_float(x.x & 0xffff0000u), a0.y);
                    a0.z = fmaf(w0, __uint_as_float(x.y << 16), a0.z); a0.w = fmaf(w1, __uint_as_float(x.y & 0xffff0000u), a0.w);
                    a1.x = fmaf(w0, __uint_as_float(y.x << 16), a1.x); a1.y = fmaf(w1, __uint_as_float(y.x & 0xffff0000u), a1.y);
                    a1.z = fmaf(w0, __uint_as_float(y.y << 16), a1.z); a1.w = fmaf(w1, __uint_as_float(y.y & 0xffff0000u), a1.w);
                };
#pragma unroll 8
                for (int j = 0; j < 56; j++) rec(j);
#pragma unroll
                for (int j = 56; j < NREC; j++) rec(j);
                if (__reduce_or_sync(0xffffffffu, bad) & 1u) {
                    poll = true;
                    if (attempt > (1u << 20)) __trap();
                    continue;
                }
                st_relaxed4(&g_state[h][2 * mi][lane], tagged4(a0.x, a0.y, a0.z, a0.w, 1u));
                st_relaxed4(&g_state[h][2 * mi + 1][lane], tagged4(a1.x, a1.y, a1.z, a1.w, 1u));
                float4 L = make_float4(fmaf(w.x, __uint_as_float(lu.x), w2.x * __uint_as_float(lv.x)), fmaf(w.y, __uint_as_float(lu.y), w2.y * __uint_as_float(lv.y)),
                                       fmaf(w.z, __uint_as_float(lu.z), w2.z * __uint_as_float(lv.z)), fmaf(w.w, __uint_as_float(lu.w), w2.w * __uint_as_float(lv.w)));
#pragma unroll
                for (int d = 16; d >= 1; d >>= 1) {
                    L.x += __shfl_xor_sync(0xffffffffu, L.x, d);
                    L.y += __shfl_xor_sync(0xffffffffu, L.y, d);
                    L.z += __shfl_xor_sync(0xffffffffu, L.z, d);
                    L.w += __shfl_xor_sync(0xffffffffu, L.w, d);
                }
                if (lane < 4) {
                    const float4 v = (lane & 1) ? L : M;
                    st_relaxed4(&g_state[h][2 * mi + (lane >> 1)][32 + (lane & 1)], tagged4(v.x, v.y, v.z, v.w, 1u));
                }
                break;
            }
            if (lane < 2) st_relaxed((unsigned int*)&g_merged[slot] + 2 * mi + lane, (unsigned)gen + 1u);
        }
    } else {
        if (lane == 0) {
            for (int s = 0; s < NST; s++) {
                mbar_init(fullK + s * 8, 1); mbar_init(fullV + s * 8, 5); mbar_init(empty0 + s * 8, 4); mbar_init(pfree0 + s * 8, 4);
            }
            for (int i = 0; i < 2; i++) mbar_init(smem_u32(&st->mfull[i]), 1);
            st->progress = 0;
            asm volatile("fence.mbarrier_init.release.cluster;" ::: "memory");
        }
        __syncwarp();
        asm volatile("bar.arrive 2, %0;" :: "n"(NTHREADS) : "memory");
        if (lane == 0) {
            uint64_t pol;
            asm volatile("createpolicy.fractional.L2::evict_first.b64 %0, 1.0;" : "=l"(pol));
            int s = 0; uint32_t ph = 1;
            int ik = 0, iv = 0;
            auto issueK = [&](uint32_t meta) {
                const uint32_t fb = fullK + ik * 8;
                if (meta & F_STOP) {
                    sts32(meta0 + ik * 4, meta);
                    mbar_arrive(fb);
                } else {
                    mbar_wait(empty0 + s * 8, ph);
                    sts32(meta0 + ik * 4, meta);
                    sts32(meta0 + NST * 4 + ik * 4, (uint32_t)s);
                    const int h = meta & 511;
                    mbar_expect_tx(fb, TILE_BYTES + ((meta & F_FIRST) ? Q_BYTES : 0));
                    tma3d(smem_base + s * TILE_BYTES, &mapK, h * SKV + (int)(meta >> 24) * TILE, fb, pol);
                    if (meta & F_FIRST) tma3d_nohint(abase + s * AUX_BYTES, &mapQ, h * SQ, fb);
                    if (++s == NST) { s = 0; ph ^= 1; }
                }
                if (++ik == NST) ik = 0;
            };
            auto issueV = [&](uint32_t meta, bool end) {
                mbar_wait(empty0 + s * 8, ph);
                const uint32_t fb = fullV + iv * 8;
                sts32(meta0 + 2 * NST * 4 + iv * 4, (uint32_t)s | (end ? V_END : 0u));
                const int h = meta & 511;
                const bool fin = (meta & (F_FIN | F_LAST)) == (F_FIN | F_LAST);
                const bool flag = (meta & (F_FIN | F_LAST)) == F_LAST && h >= RG;
                mbar_expect_tx(fb, TILE_BYTES + (fin ? ST_BYTES : 0) + (flag ? 16 : 0));
                tma3d(smem_base + s * TILE_BYTES, &mapV, h * SKV + (int)(meta >> 24) * TILE, fb, pol);
                if (fin)  bulk_load(abase + s * AUX_BYTES, &g_state[h][0][0], ST_BYTES, fb);
                if (flag) bulk_load(abase + s * AUX_BYTES, &g_merged[h % RG], 16, fb);
                if (++s == NST) { s = 0; ph ^= 1; }
                if (++iv == NST) iv = 0;
            };
            auto first_tile = [&](int u) -> uint32_t {
                if (u >= NTOTAL) return F_STOP;
                if (u >= NMAIN) return (uint32_t)(u - NMAIN) | F_FIN | F_FIRST | ((uint32_t)NREC << 24);
                const uint32_t h = (uint32_t)u / (uint32_t)NREC, j = (uint32_t)u - h * (uint32_t)NREC;
                return h | F_FIRST | F_LAST | (j << 24);
            };
            const unsigned int last_claim = (unsigned)(NTOTAL - G - 1);
            uint32_t cur = first_tile(cta);
            int claim = cta - G;
            issueK(cur);
            while (true) {
                uint32_t nxt;
                if (cur & F_LAST) {
                    const int u = claim + 2 * G;
                    st->progress = u;
                    nxt = first_tile(u);
                } else {
                    nxt = ((cur & ~F_FIRST) | F_LAST) + (1u << 24);
                }
                if (nxt & F_LAST) claim = (int)atom_inc(&g_ctr[0], last_claim);
                issueK(nxt);
                issueV(cur, (nxt & F_STOP) != 0u);
                if (nxt & F_STOP) break;
                cur = nxt;
            }
        }
    }
}

typedef CUresult (*EncodeFn)(CUtensorMap*, CUtensorMapDataType, cuuint32_t, void*, const cuuint64_t*, const cuuint64_t*,
                             const cuuint32_t*, const cuuint32_t*, CUtensorMapInterleave, CUtensorMapSwizzle,
                             CUtensorMapL2promotion, CUtensorMapFloatOOBfill);

void make_map(EncodeFn enc, CUtensorMap* m, const void* p, int rows, int box_rows) {
    cuuint64_t gd[3] = {64, (cuuint64_t)rows, 2};
    cuuint64_t gs[2] = {256, 128};
    cuuint32_t bd[3] = {64, (cuuint32_t)box_rows, 2};
    cuuint32_t es[3] = {1, 1, 1};
    enc(m, CU_TENSOR_MAP_DATA_TYPE_BFLOAT16, 3, const_cast<void*>(p), gd, gs, bd, es, CU_TENSOR_MAP_INTERLEAVE_NONE,
        CU_TENSOR_MAP_SWIZZLE_128B, CU_TENSOR_MAP_L2_PROMOTION_L2_256B, CU_TENSOR_MAP_FLOAT_OOB_FILL_NONE);
}

}

extern "C" void kernel_launch(void* const* d_in, const int* in_sizes, int n_in, void* d_out, int out_size) {
    (void)in_sizes; (void)n_in; (void)out_size;
    static EncodeFn enc = nullptr;
    static int grid = 0;
    if (!enc) {
        cudaDriverEntryPointQueryResult qr;
        cudaGetDriverEntryPoint("cuTensorMapEncodeTiled", (void**)&enc, cudaEnableDefault, &qr);
        int dev = 0, sms = 0;
        cudaGetDevice(&dev);
        cudaDeviceGetAttribute(&sms, cudaDevAttrMultiProcessorCount, dev);
        grid = sms;
        cudaFuncSetAttribute(attn_kernel, cudaFuncAttributeMaxDynamicSharedMemorySize, SMEM_BYTES);
    }
    CUtensorMap mk, mv, mq;
    make_map(enc, &mq, d_in[0], NH * SQ, SQ);
    make_map(enc, &mk, d_in[1], NH * SKV, TILE);
    make_map(enc, &mv, d_in[2], NH * SKV, TILE);
    attn_kernel<<<grid, NTHREADS, SMEM_BYTES>>>(mk, mv, mq, (__nv_bfloat16*)d_out);
}
```
